```python
import torch

def _softmax(x, axis=-1):
    return torch.softmax(x, dim=axis)
def _gelu(x):
    return torch.nn.functional.gelu(x, approximate="tanh")
def _silu(x):
    return torch.nn.functional.silu(x)
def _sigmoid(x):
    return torch.sigmoid(x)
def _layernorm(x, axis=-1, eps=1e-5):
    m = x.mean(dim=axis, keepdim=True)
    v = x.var(dim=axis, keepdim=True, unbiased=False)
    return (x - m) / torch.sqrt(v + eps)
def _scatter_add(tgt, idx, src, axis=0):
    return tgt.clone().index_add_(axis, idx, src)
def _segment_sum(src, seg, n):
    out = torch.zeros((n,) + src.shape[1:], dtype=src.dtype)
    return out.index_add_(0, seg, src)
def _pad(x, pw):
    flat = tuple(v for pair in reversed(pw) for v in pair)
    return torch.nn.functional.pad(x, flat)

kernel_name = 'gated_mix__ssm_conv_s4__dense_activation_squared_relu__prompt'

def setup_inputs():

    _w = (lambda a: (lambda t: t.to(torch.bfloat16) if t.is_floating_point() else t)(torch.as_tensor(a)))
    def _A_setup():
        B, L, D, N = 1, 2048, 640, 192
        A_re = -(lambda _x: torch.exp(torch.as_tensor(_x)))((lambda *s: torch.randn(*s, dtype=torch.bfloat16) * 6.4)(D, N))
        A_im = torch.pi * (lambda *s: torch.randn(*s, dtype=torch.bfloat16) * 0.1)(D, N)
        B_re = (lambda *s: torch.randn(*s, dtype=torch.bfloat16) * 0.2)(D, N)
        B_im = (lambda *s: torch.randn(*s, dtype=torch.bfloat16) * 0.2)(D, N)
        C_re = (lambda *s: torch.randn(*s, dtype=torch.bfloat16) * 0.2)(D, N)
        C_im = (lambda *s: torch.randn(*s, dtype=torch.bfloat16) * 0.2)(D, N)
        log_dt = (lambda *s: torch.randn(*s, dtype=torch.bfloat16) * 0.1)(D) * 0.5 - 4.0
        Dskip = (lambda *s: torch.randn(*s, dtype=torch.bfloat16) * 0.1)(D)
        return {
            "u": _w((lambda *s: torch.randn(*s, dtype=torch.bfloat16) * 0.05)(B, L, D)),
            "A_re": _w(A_re),
            "A_im": _w(A_im),
            "B_re": _w(B_re),
            "B_im": _w(B_im),
            "C_re": _w(C_re),
            "C_im": _w(C_im),
            "log_dt": _w(log_dt),
            "Dskip": _w(Dskip),
        }
    _A_in = _A_setup()

    def _B_setup():
        B, S, D, F = 1, 2048, 640, 1536
        return {
            "x": _w((lambda *s: torch.randn(*s, dtype=torch.bfloat16) * 0.05)(B, S, D)),
            "w1": _w((lambda *s: torch.randn(*s, dtype=torch.bfloat16) * 0.05)(D, F)),
            "b1": _w((lambda *s: torch.randn(*s, dtype=torch.bfloat16) * 0.05)(F)),
            "w2": _w((lambda *s: torch.randn(*s, dtype=torch.bfloat16) * 0.05)(F, D)),
            "b2": _w((lambda *s: torch.randn(*s, dtype=torch.bfloat16) * 0.05)(D)),
        }
    _B_in = _B_setup()

    return {
        "A_u": _A_in["u"],
        "A_A_re": _A_in["A_re"],
        "A_A_im": _A_in["A_im"],
        "A_B_re": _A_in["B_re"],
        "A_B_im": _A_in["B_im"],
        "A_C_re": _A_in["C_re"],
        "A_C_im": _A_in["C_im"],
        "A_log_dt": _A_in["log_dt"],
        "A_Dskip": _A_in["Dskip"],
        "B_x": _B_in["x"],
        "B_w1": _B_in["w1"],
        "B_b1": _B_in["b1"],
        "B_w2": _B_in["w2"],
        "B_b2": _B_in["b2"],
        "gate_w": _w((lambda *s: torch.randn(*s, dtype=torch.bfloat16) * 0.05)(640) * 16.0),
    }

def reference(A_u, A_A_re, A_A_im, A_B_re, A_B_im, A_C_re, A_C_im, A_log_dt, A_Dskip, B_x, B_w1, B_b1, B_w2, B_b2, gate_w):
    def _A_ref(u, A_re, A_im, B_re, B_im, C_re, C_im, log_dt, Dskip):
        Bsz, L, D = u.shape
        dt = torch.exp(log_dt)[:, None]
        A = A_re + 1j * A_im
        Bc = B_re + 1j * B_im
        Cc = C_re + 1j * C_im
        logdA = dt * A
        dB = dt * Bc
        l = (lambda x, dt: x.to(dt))(torch.arange(L), A_re.dtype)
        P = torch.exp(logdA[:, :, None] * l[None, None, :])
        K = torch.einsum("dn,dnl,dn->dl", Cc, P, dB).real
        L2 = 2 * L
        Kp = _pad(K, ((0, 0), (0, L)))
        up = (lambda x, *d: x.permute(*d))(u, 0, 2, 1)
        up = _pad(up, ((0, 0), (0, 0), (0, L)))
        Kf = (lambda x, axes=(-2,-1): torch.fft.rfft2(x.float(), dim=axes))(Kp[:, None, :], axes=(-2, -1))
        Uf = (lambda x, axes=(-2,-1): torch.fft.rfft2(x.float(), dim=axes))(up[:, :, None, :], axes=(-2, -1))
        Yf = Uf * Kf[None, :, :, :]
        y = (lambda x, s, axes=(-2,-1): torch.fft.irfft2(x, s=s, dim=axes).to(torch.bfloat16))(Yf, (1, L2), axes=(-2, -1))[:, :, 0, :L]
        y = (lambda x, *d: x.permute(*d))(y, 0, 2, 1) + u * Dskip[None, None, :]
        return y

    def _B_ref(x, w1, b1, w2, b2):
        h = torch.einsum("bsd,df->bsf", x, w1) + b1
        zero = torch.zeros_like(h)
        r = torch.where(h > zero, h, zero)
        h = r * r
        out = torch.einsum("bsf,fd->bsd", h, w2) + b2
        return out

    x = A_u
    g = _sigmoid((x * gate_w).sum(-1, keepdims=True))
    a = _A_ref(x, A_A_re, A_A_im, A_B_re, A_B_im, A_C_re, A_C_im, A_log_dt, A_Dskip)
    b = _B_ref(x, B_w1, B_b1, B_w2, B_b2)
    return g * a + (1 - g) * b
```

```cpp
#include <cuda_runtime.h>
#include <cuda_bf16.h>
#include <cuda.h>
#include <stdint.h>
#include <string.h>

typedef __nv_bfloat16 bf16;
typedef __nv_bfloat162 bf162;

constexpr int L_ = 2048, D_ = 640, NM_ = 192, F_ = 1536;
constexpr int NCTA = 130;

__device__ bf16 g_h[L_ * F_];
__device__ bf16 g_aT[D_ * L_];
__device__ bf16 g_gate[L_];
__device__ unsigned g_hflag[128 * 8];
__device__ unsigned g_aflag[8 * 32];
__device__ unsigned g_epoch[NCTA];
__device__ unsigned g_err;
#define TS(i)
#define TR(i)

#define SPIN_LIMIT 2000000
#define SPIN_FAIL __trap()
__device__ __forceinline__ uint32_t smem_u32(const void* p) { return (uint32_t)__cvta_generic_to_shared(p); }
__device__ __forceinline__ void mbar_init(uint32_t bar, uint32_t cnt) {
  asm volatile("mbarrier.init.shared::cta.b64 [%0], %1;" ::"r"(bar), "r"(cnt) : "memory");
}
__device__ __forceinline__ void mbar_arrive(uint32_t bar) {
  asm volatile("mbarrier.arrive.shared::cta.b64 _, [%0];" ::"r"(bar) : "memory");
}
__device__ __forceinline__ void mbar_expect_tx(uint32_t bar, uint32_t bytes) {
  asm volatile("mbarrier.arrive.expect_tx.shared::cta.b64 _, [%0], %1;" ::"r"(bar), "r"(bytes) : "memory");
}
__device__ __forceinline__ bool mbar_try(uint32_t bar, uint32_t parity) {
  uint32_t ok;
  asm volatile("{.reg .pred p; mbarrier.try_wait.parity.shared::cta.b64 p, [%1], %2; selp.u32 %0,1,0,p;}"
               : "=r"(ok) : "r"(bar), "r"(parity) : "memory");
  return ok != 0;
}
__device__ __forceinline__ void mbar_wait(uint32_t bar, uint32_t parity) {
  asm volatile(
      "{\n.reg .pred p;\n.reg .u32 c;\nmov.u32 c, 0;\n"
      "WL:\nmbarrier.try_wait.parity.shared::cta.b64 p, [%0], %1;\n@p bra WD;\n"
      "add.u32 c, c, 1;\nsetp.lt.u32 p, c, 4000000;\n@p bra WL;\ntrap;\nWD:\n}"
      ::"r"(bar), "r"(parity) : "memory");
}
__device__ __forceinline__ void tma_load2d(uint32_t dst, const CUtensorMap* tm, int c0, int c1, uint32_t bar) {
  asm volatile("cp.async.bulk.tensor.2d.shared::cluster.global.mbarrier::complete_tx::bytes [%0], [%1, {%3, %4}], [%2];"
               ::"r"(dst), "l"(tm), "r"(bar), "r"(c0), "r"(c1) : "memory");
}
__device__ __forceinline__ void tma_load2d_mc(uint32_t dst, const CUtensorMap* tm, int c0, int c1, uint32_t bar) {
  asm volatile("cp.async.bulk.tensor.2d.shared::cluster.global.mbarrier::complete_tx::bytes.multicast::cluster [%0], [%1, {%3, %4}], [%2], %5;"
               ::"r"(dst), "l"(tm), "r"(bar), "r"(c0), "r"(c1), "h"((uint16_t)3) : "memory");
}
__device__ __forceinline__ void tma_load3d_mc(uint32_t dst, const CUtensorMap* tm, int c0, int c1, int c2, uint32_t bar) {
  asm volatile("cp.async.bulk.tensor.3d.shared::cluster.global.mbarrier::complete_tx::bytes.multicast::cluster [%0], [%1, {%3, %4, %5}], [%2], %6;"
               ::"r"(dst), "l"(tm), "r"(bar), "r"(c0), "r"(c1), "r"(c2), "h"((uint16_t)3) : "memory");
}
__device__ __forceinline__ void l2_prefetch(const void* p, uint32_t bytes) {
  asm volatile("cp.async.bulk.prefetch.L2.global [%0], %1;" ::"l"(p), "r"(bytes) : "memory");
}
__device__ __forceinline__ void prefetch_tmap(const CUtensorMap* tm) { asm volatile("prefetch.tensormap [%0];" ::"l"(tm) : "memory"); }
__device__ __forceinline__ uint32_t mapa(uint32_t addr, uint32_t rank) {
  uint32_t r;
  asm("mapa.shared::cluster.u32 %0, %1, %2;" : "=r"(r) : "r"(addr), "r"(rank));
  return r;
}
__device__ __forceinline__ void mbar_arrive_cluster(uint32_t bar) {
  asm volatile("mbarrier.arrive.shared::cluster.b64 _, [%0];" ::"r"(bar) : "memory");
}
__device__ __forceinline__ void mbar_wait_cluster(uint32_t bar, uint32_t parity) { mbar_wait(bar, parity); }
__device__ __forceinline__ void cluster_arrive() { asm volatile("barrier.cluster.arrive.relaxed.aligned;" ::: "memory"); }
__device__ __forceinline__ void cluster_wait() { asm volatile("barrier.cluster.wait.aligned;" ::: "memory"); }
__device__ __forceinline__ void stsm_x4_t(uint32_t addr, uint32_t a, uint32_t b, uint32_t c, uint32_t d) {
  asm volatile("stmatrix.sync.aligned.m8n8.x4.trans.shared.b16 [%0], {%1,%2,%3,%4};" ::"r"(addr), "r"(a), "r"(b), "r"(c), "r"(d) : "memory");
}
__device__ __forceinline__ void tma_store2d(const CUtensorMap* tm, uint32_t src, int c0, int c1) {
  asm volatile("cp.async.bulk.tensor.2d.global.shared::cta.bulk_group [%0, {%2, %3}], [%1];"
               ::"l"(tm), "r"(src), "r"(c0), "r"(c1) : "memory");
}
__device__ __forceinline__ void bulk_store(void* dst, uint32_t src, uint32_t bytes) {
  asm volatile("cp.async.bulk.global.shared::cta.bulk_group [%0], [%1], %2;" ::"l"(dst), "r"(src), "r"(bytes) : "memory");
}
__device__ __forceinline__ void bulk_commit() { asm volatile("cp.async.bulk.commit_group;" ::: "memory"); }
__device__ __forceinline__ void bulk_wait_read0() { asm volatile("cp.async.bulk.wait_group.read 0;" ::: "memory"); }
__device__ __forceinline__ void bulk_wait0() { asm volatile("cp.async.bulk.wait_group 0;" ::: "memory"); }
__device__ __forceinline__ void fence_async_smem() { asm volatile("fence.proxy.async.shared::cta;" ::: "memory"); }
__device__ __forceinline__ void fence_async_all() { asm volatile("fence.proxy.async;" ::: "memory"); }
__device__ __forceinline__ void named_bar(int id, int n) { asm volatile("bar.sync %0, %1;" ::"r"(id), "r"(n) : "memory"); }
__device__ __forceinline__ void named_arrive(int id, int n) { asm volatile("bar.arrive %0, %1;" ::"r"(id), "r"(n) : "memory"); }
__device__ __forceinline__ void wg_fence() { asm volatile("wgmma.fence.sync.aligned;" ::: "memory"); }
__device__ __forceinline__ void wg_commit() { asm volatile("wgmma.commit_group.sync.aligned;" ::: "memory"); }
template <int N> __device__ __forceinline__ void wg_wait() { asm volatile("wgmma.wait_group.sync.aligned %0;" ::"n"(N) : "memory"); }
__device__ __forceinline__ uint64_t make_desc(uint32_t addr, uint32_t lbo, uint32_t sbo, uint32_t swz) {
  return (uint64_t)((addr & 0x3FFFF) >> 4) | ((uint64_t)(lbo >> 4) << 16) | ((uint64_t)(sbo >> 4) << 32) | ((uint64_t)swz << 62);
}
__device__ __forceinline__ void red_release_add(unsigned* p, unsigned v) {
  asm volatile("red.release.gpu.global.add.u32 [%0], %1;" ::"l"(p), "r"(v) : "memory");
}
__device__ __forceinline__ void red_relaxed_add(unsigned* p, unsigned v) {
  asm volatile("red.relaxed.gpu.global.add.u32 [%0], %1;" ::"l"(p), "r"(v) : "memory");
}
__device__ __forceinline__ unsigned ld_relaxed(const unsigned* p) {
  unsigned v;
  asm volatile("ld.relaxed.gpu.global.u32 %0, [%1];" : "=r"(v) : "l"(p) : "memory");
  return v;
}
__device__ __forceinline__ unsigned ld_acquire(const unsigned* p) {
  unsigned v;
  asm volatile("ld.acquire.gpu.global.u32 %0, [%1];" : "=r"(v) : "l"(p) : "memory");
  return v;
}
__device__ __forceinline__ void flag_wait(const unsigned* p, unsigned target) {
  for (int it = 0; it < 2000000; ++it) {
    if ((int)(ld_acquire(p) - target) >= 0) return;
    __nanosleep(32);
  }
  g_err = 2;
}
__device__ __forceinline__ void stsm_x4(uint32_t addr, uint32_t a, uint32_t b, uint32_t c, uint32_t d) {
  asm volatile("stmatrix.sync.aligned.m8n8.x4.shared.b16 [%0], {%1,%2,%3,%4};" ::"r"(addr), "r"(a), "r"(b), "r"(c), "r"(d) : "memory");
}
__device__ __forceinline__ void ldsm_x4(uint32_t addr, uint32_t& a, uint32_t& b, uint32_t& c, uint32_t& d) {
  asm volatile("ldmatrix.sync.aligned.m8n8.x4.shared.b16 {%0,%1,%2,%3}, [%4];" : "=r"(a), "=r"(b), "=r"(c), "=r"(d) : "r"(addr) : "memory");
}
__device__ __forceinline__ void ldsm_x4_t(uint32_t addr, uint32_t& a, uint32_t& b, uint32_t& c, uint32_t& d) {
  asm volatile("ldmatrix.sync.aligned.m8n8.x4.trans.shared.b16 {%0,%1,%2,%3}, [%4];" : "=r"(a), "=r"(b), "=r"(c), "=r"(d) : "r"(addr) : "memory");
}
__device__ __forceinline__ uint32_t pack_bf16(float lo, float hi) {
  uint32_t r;
  asm("cvt.rn.bf16x2.f32 %0, %1, %2;" : "=r"(r) : "f"(hi), "f"(lo));
  return r;
}
__device__ __forceinline__ uint32_t as_u32(bf162 v) { return *reinterpret_cast<uint32_t*>(&v); }
__device__ __forceinline__ bf162 as_bf162(uint32_t v) { return *reinterpret_cast<bf162*>(&v); }

#define R8(d, b) "+f"(d[b + 0]), "+f"(d[b + 1]), "+f"(d[b + 2]), "+f"(d[b + 3]), "+f"(d[b + 4]), "+f"(d[b + 5]), "+f"(d[b + 6]), "+f"(d[b + 7])
__device__ __forceinline__ void wgmma_n192(float* d, uint64_t da, uint64_t db) {
  asm volatile(
      "wgmma.mma_async.sync.aligned.m64n192k16.f32.bf16.bf16 "
      "{%0,%1,%2,%3,%4,%5,%6,%7,%8,%9,%10,%11,%12,%13,%14,%15,%16,%17,%18,%19,%20,%21,%22,%23,%24,%25,%26,%27,%28,%29,%30,%31,"
      "%32,%33,%34,%35,%36,%37,%38,%39,%40,%41,%42,%43,%44,%45,%46,%47,%48,%49,%50,%51,%52,%53,%54,%55,%56,%57,%58,%59,%60,%61,%62,%63,"
      "%64,%65,%66,%67,%68,%69,%70,%71,%72,%73,%74,%75,%76,%77,%78,%79,%80,%81,%82,%83,%84,%85,%86,%87,%88,%89,%90,%91,%92,%93,%94,%95}, "
      "%96, %97, 1, 1, 1, 0, 1;"
      : R8(d, 0), R8(d, 8), R8(d, 16), R8(d, 24), R8(d, 32), R8(d, 40), R8(d, 48), R8(d, 56), R8(d, 64), R8(d, 72), R8(d, 80), R8(d, 88)
      : "l"(da), "l"(db));
}
__device__ __forceinline__ void wgmma_n80(float* d, uint64_t da, uint64_t db) {
  asm volatile(
      "wgmma.mma_async.sync.aligned.m64n80k16.f32.bf16.bf16 "
      "{%0,%1,%2,%3,%4,%5,%6,%7,%8,%9,%10,%11,%12,%13,%14,%15,%16,%17,%18,%19,%20,%21,%22,%23,%24,%25,%26,%27,%28,%29,%30,%31,"
      "%32,%33,%34,%35,%36,%37,%38,%39}, %40, %41, 1, 1, 1, 1, 0;"
      : R8(d, 0), R8(d, 8), R8(d, 16), R8(d, 24), R8(d, 32)
      : "l"(da), "l"(db));
}

__device__ __forceinline__ void wgmma_n48_rs(float* d, const uint32_t* a, uint64_t db) {
  asm volatile(
      "wgmma.mma_async.sync.aligned.m64n48k16.f32.bf16.bf16 "
      "{%0,%1,%2,%3,%4,%5,%6,%7,%8,%9,%10,%11,%12,%13,%14,%15,%16,%17,%18,%19,%20,%21,%22,%23}, "
      "{%24,%25,%26,%27}, %28, 1, 1, 1, 0;"
      : R8(d, 0), R8(d, 8), R8(d, 16)
      : "r"(a[0]), "r"(a[1]), "r"(a[2]), "r"(a[3]), "l"(db));
}
__device__ __forceinline__ void mma16816(float* d, uint32_t a0, uint32_t a1, uint32_t a2, uint32_t a3, uint32_t b0, uint32_t b1) {
  asm("mma.sync.aligned.m16n8k16.row.col.f32.bf16.bf16.f32 {%0,%1,%2,%3}, {%4,%5,%6,%7}, {%8,%9}, {%0,%1,%2,%3};"
      : "+f"(d[0]), "+f"(d[1]), "+f"(d[2]), "+f"(d[3]) : "r"(a0), "r"(a1), "r"(a2), "r"(a3), "r"(b0), "r"(b1));
}
__device__ __forceinline__ uint32_t lds32(uint32_t a) { uint32_t v; asm volatile("ld.shared.u32 %0, [%1];" : "=r"(v) : "r"(a)); return v; }
__device__ __forceinline__ uint32_t lds16(uint32_t a) { uint16_t v; asm volatile("ld.shared.u16 %0, [%1];" : "=h"(v) : "r"(a)); return v; }
__device__ __forceinline__ float2 lds64f(uint32_t a) { float2 v; asm volatile("ld.shared.v2.f32 {%0,%1}, [%2];" : "=f"(v.x), "=f"(v.y) : "r"(a)); return v; }
__device__ __forceinline__ float4 lds128f(uint32_t a) { float4 v; asm volatile("ld.shared.v4.f32 {%0,%1,%2,%3}, [%4];" : "=f"(v.x), "=f"(v.y), "=f"(v.z), "=f"(v.w) : "r"(a)); return v; }
__device__ __forceinline__ uint2 lds64u(uint32_t a) { uint2 v; asm volatile("ld.shared.v2.u32 {%0,%1}, [%2];" : "=r"(v.x), "=r"(v.y) : "r"(a)); return v; }
__device__ __forceinline__ uint4 lds128u(uint32_t a) { uint4 v; asm volatile("ld.shared.v4.u32 {%0,%1,%2,%3}, [%4];" : "=r"(v.x), "=r"(v.y), "=r"(v.z), "=r"(v.w) : "r"(a)); return v; }
__device__ __forceinline__ void sts16(uint32_t a, uint32_t v) { asm volatile("st.shared.u16 [%0], %1;" ::"r"(a), "h"((uint16_t)v) : "memory"); }
__device__ __forceinline__ void sts32(uint32_t a, uint32_t v) { asm volatile("st.shared.u32 [%0], %1;" ::"r"(a), "r"(v) : "memory"); }
__device__ __forceinline__ void sts32f(uint32_t a, float v) { asm volatile("st.shared.f32 [%0], %1;" ::"r"(a), "f"(v) : "memory"); }
__device__ __forceinline__ void sts64f(uint32_t a, float x, float y) { asm volatile("st.shared.v2.f32 [%0], {%1,%2};" ::"r"(a), "f"(x), "f"(y) : "memory"); }
__device__ __forceinline__ void sts128f(uint32_t a, float x, float y, float z, float w) { asm volatile("st.shared.v4.f32 [%0], {%1,%2,%3,%4};" ::"r"(a), "f"(x), "f"(y), "f"(z), "f"(w) : "memory"); }
__device__ __forceinline__ void sts128u(uint32_t a, uint32_t x, uint32_t y, uint32_t z, uint32_t w) { asm volatile("st.shared.v4.u32 [%0], {%1,%2,%3,%4};" ::"r"(a), "r"(x), "r"(y), "r"(z), "r"(w) : "memory"); }
__device__ __forceinline__ void ldsm4(uint32_t addr, uint32_t* r) {
  asm volatile("ldmatrix.sync.aligned.m8n8.x4.shared.b16 {%0,%1,%2,%3}, [%4];" : "=r"(r[0]), "=r"(r[1]), "=r"(r[2]), "=r"(r[3]) : "r"(addr));
}
__device__ __forceinline__ void ldsm4t(uint32_t addr, uint32_t* r) {
  asm volatile("ldmatrix.sync.aligned.m8n8.x4.trans.shared.b16 {%0,%1,%2,%3}, [%4];" : "=r"(r[0]), "=r"(r[1]), "=r"(r[2]), "=r"(r[3]) : "r"(addr));
}
__device__ __forceinline__ float bf_lo(uint32_t v) { return __uint_as_float(v << 16); }
__device__ __forceinline__ float bf_hi(uint32_t v) { return __uint_as_float(v & 0xffff0000u); }
__device__ __forceinline__ float ldbf(const bf16* p) { return __uint_as_float((uint32_t)__ldg((const unsigned short*)p) << 16); }
__device__ __forceinline__ float2 cmul(float2 a, float2 b) { return make_float2(fmaf(a.x, b.x, -a.y * b.y), fmaf(a.x, b.y, a.y * b.x)); }
__device__ __forceinline__ float2 csqr(float2 a) { return make_float2(fmaf(a.x, a.x, -a.y * a.y), (a.x + a.x) * a.y); }
__device__ __forceinline__ float2 csub(float2 a, float2 b) { return make_float2(a.x - b.x, a.y - b.y); }
__device__ __forceinline__ float2 cexp_p2(float ar2, float fh, float fl, float l) {
  float m;
  asm("ex2.approx.f32 %0, %1;" : "=f"(m) : "f"(ar2 * l));
  float ph = fh * l;
  ph = fmaf(fl, l, ph - rintf(ph)) * 6.283185307f;
  return make_float2(m * __cosf(ph), m * __sinf(ph));
}
__device__ __forceinline__ uint32_t packB(float2 p) { return pack_bf16(p.x, -p.y); }

constexpr int G1_STAGES = 3, G1_TX = 40960;
constexpr int SM_X = 0;
constexpr int SM_W = 49152;
constexpr int G2_STAGES = 7, G2_STAGE_BYTES = 26624;
constexpr int G2_EARLY = 3;
constexpr int SM_AT = G2_STAGES * G2_STAGE_BYTES;
constexpr int SM_OUT = SM_AT + 20480;
constexpr int U0_BYTES = 5200;
constexpr int KT_K0 = 0, KT_E1 = 1088, KT_O1 = 1280, KT_E2 = 1472, KT_O2 = 1792, KT_E3 = 2112, KT_O3 = 2432, KT_BYTES = 2752;
constexpr int WS_U4 = 0, WS_W3A = 3616, WS_W3B = 7216, WS_W5 = 10816, WS_W9 = 13904, WS_W7 = 15984, WS_BYTES = 18064;
constexpr int WS_P = WS_W5 + 16 - 250 * 4;
constexpr int SM_U0 = 122880, SM_KT = SM_U0 + 5 * U0_BYTES, SM_WS = SM_KT + 5 * KT_BYTES, SM_WSHI = 122880 - 2 * WS_BYTES;
constexpr int SM_USTG = (SM_WS + 127) & ~127;
constexpr int KG_BYTES = 13056, KG_T = 6912;
constexpr int SM_MISC = 229376;
constexpr int SM_KG = SM_MISC - 2 * KG_BYTES;
static_assert(SM_USTG + 32768 <= SM_WS + 2 * WS_BYTES && SM_KG >= SM_WS + 2 * WS_BYTES && SM_WS + 3 * WS_BYTES <= SM_MISC, "smem");
static_assert(SM_WSHI >= G2_EARLY * G2_STAGE_BYTES, "smem");
constexpr int SM_B1 = SM_MISC + 512;
constexpr int SM_GATE = SM_B1 + 384;
constexpr int SM_GOUT = SM_GATE + 160;
constexpr int SM_CTR = SM_GOUT + 32;
constexpr int SM_TR = SM_MISC + 1280;
constexpr int SM_TOTAL = SM_MISC + 2048;
constexpr int SMEM_BYTES = SM_TOTAL + 1024;
constexpr int NCONV_WARPS = 14;

struct Params {
  const bf16 *u, *Are, *Aim, *Bre, *Bim, *Cre, *Cim, *logdt, *Dsk, *w1, *b1, *w2, *b2, *gate_w;
};

__device__ __forceinline__ uint32_t u0_chunk(uint32_t u0, int m) { return u0 + (m >> 2) * 80 + (m & 3) * 16; }

__device__ __forceinline__ void build_w(uint32_t ws, uint32_t u0, int m) {
  if (m > 223) return;
  const uint2 c0 = lds64u(u0_chunk(u0, m - 1) + 8);
  const uint4 c1 = lds128u(u0_chunk(u0, m)), c2 = lds128u(u0_chunk(u0, m + 1));
  const uint32_t w[10] = {c0.x, c0.y, c1.x, c1.y, c1.z, c1.w, c2.x, c2.y, c2.z, c2.w};
  float q[20];
  q[0] = 0.f;
#pragma unroll
  for (int k = 0; k < 19; k++) q[k + 1] = q[k] + ((k & 1) ? bf_hi(w[k >> 1]) : bf_lo(w[k >> 1]));
#define WIN(hi, lo) pack_bf16(q[hi] - q[lo], q[hi + 1] - q[lo + 1]), pack_bf16(q[hi + 2] - q[lo + 2], q[hi + 3] - q[lo + 3]), \
                    pack_bf16(q[hi + 4] - q[lo + 4], q[hi + 5] - q[lo + 5]), pack_bf16(q[hi + 6] - q[lo + 6], q[hi + 7] - q[lo + 7])
  const uint32_t o = ws + (m + 1) * 16;
  if (m >= -1) {
    sts128u(o + WS_U4, c1.z, c1.w, c2.x, c2.y);
    sts128u(o + WS_W3A, WIN(8, 5));
    sts128u(o + WS_W3B, WIN(12, 9));
    if (m <= 191) sts128u(o + WS_W5, WIN(9, 4));
    if (m <= 128) sts128u(o + WS_W7, WIN(8, 1));
  }
  if (m <= 127) sts128u(o + 16 + WS_W9, WIN(9, 0));
#undef WIN
}

__device__ __forceinline__ void conv_seg1(uint32_t ws, uint32_t u0, uint32_t kt, uint32_t bar_prev, int lane) {
  const int g = lane >> 2, c = lane & 3;
  uint32_t RE[10], RO[10];
  {
    const uint32_t a = kt + KT_E1 + (86 - 2 * g + 2 * c) * 2;
#pragma unroll
    for (int k = 0; k < 10; k++) { RE[k] = lds32(a - 16 * k); RO[k] = lds32(a + (KT_O1 - KT_E1) - 16 * k); }
  }
  const int mi = lane >> 3, lam = (lane & 7) + 8 * (mi & 1);
  uint32_t addr = ws + ((lam >> 1) - 7) * 16 + (mi < 2 ? ((lam & 1) ? WS_W3B : WS_W3A) : WS_U4), stride = 128;
  if (mi >= 2 && (lam & 1)) { addr = u0_chunk(u0, ((lam + 1) >> 1) - 8); stride = 160; }
  float acc[14][4];
#pragma unroll
  for (int i = 0; i < 14; i++) acc[i][0] = acc[i][1] = acc[i][2] = acc[i][3] = 0.f;
#define RA(R, e) (((e) < -8 || (e) > 64) ? 0u : R[((e) < -8 || (e) > 64) ? 0 : ((e) + 8) / 8])
#pragma unroll
  for (int k = 0; k < 29; k++) {
    uint32_t b[4];
    ldsm4t((k == 0 && lam < 14) ? u0 - 80 : addr, b);
    addr += stride;
#pragma unroll
    for (int mt = 0; mt < 14; mt++) {
      const int e = 32 * mt - 16 * k + 16;
      if (e >= -16 && e <= 64) mma16816(acc[mt], RA(RE, e), RA(RE, e + 16), RA(RE, e - 8), RA(RE, e + 8), b[0], b[1]);
    }
#pragma unroll
    for (int mt = 0; mt < 14; mt++) {
      const int e = 32 * mt - 16 * k + 16;
      if (e >= -16 && e <= 64) mma16816(acc[mt], RA(RO, e), RA(RO, e + 16), RA(RO, e - 8), RA(RO, e + 8), b[2], b[3]);
    }
  }
#undef RA
  const float head = bf_lo(lds16(kt + KT_E1 + 156)) * bf_lo(lds16(ws + WS_W3A + (lane & 7) * 2));
  mbar_wait(bar_prev, 0);
  const uint32_t pa = ws + WS_P + (258 + 8 * g + 2 * c) * 4;
#pragma unroll
  for (int mt = 0; mt < 14; mt++)
#pragma unroll
    for (int h = 0; h < 2; h++) {
      const uint32_t a = pa + (16 * mt + 8 * h) * 32;
      float x = acc[mt][2 * h], y = acc[mt][2 * h + 1];
      if (mt >= 2 || (mt == 1 && h == 1 && g == 7)) { const float2 o = lds64f(a); x += o.x; y += o.y; }
      sts64f(a, x, y);
    }
  if (lane < 8) sts32f(ws + WS_P + (250 + lane) * 4, head);
}

__device__ __forceinline__ void load_tab9(uint32_t tb, int g, int c, uint32_t* R) {
  const uint32_t a = tb + (g & 1) * 160 + (72 + (g & 1) - g + 2 * c) * 2;
#pragma unroll
  for (int k = 0; k < 9; k++) R[k] = lds32(a - 16 * k);
}
#define RB(R, e) (((e) < 0 || (e) > 64) ? 0u : R[((e) < 0 || (e) > 64) ? 0 : (e) / 8])
__device__ __forceinline__ void conv_seg2(uint32_t ws, uint32_t u0, uint32_t kt, uint32_t bar_prev, int lane) {
  const int g = lane >> 2, c = lane & 3;
  uint32_t RE[9], RO[9];
  load_tab9(kt + KT_E2, g, c, RE);
  load_tab9(kt + KT_O2, g, c, RO);
  const int mi = lane >> 3, lam = (lane & 7) + 8 * (mi & 1);
  const uint32_t addr = ws + (lam - 15) * 16 + (mi < 2 ? WS_W5 : WS_W3B);
  float acc[12][4];
#pragma unroll
  for (int i = 0; i < 12; i++) acc[i][0] = acc[i][1] = acc[i][2] = acc[i][3] = 0.f;
#pragma unroll
  for (int k = 0; k < 13; k++) {
    uint32_t b[4];
    ldsm4t((k == 0 && lam < 15) ? u0 - 80 : addr + k * 256, b);
#pragma unroll
    for (int mt = 0; mt < 12; mt++) {
      const int e = 16 * (mt - k + 1);
      if (e >= 0 && e <= 64) mma16816(acc[mt], RB(RE, e), RB(RE, e + 8), RB(RE, e - 8), RB(RE, e), b[0], b[1]);
    }
#pragma unroll
    for (int mt = 0; mt < 12; mt++) {
      const int e = 16 * (mt - k + 1);
      if (e >= 0 && e <= 64) mma16816(acc[mt], RB(RO, e), RB(RO, e + 8), RB(RO, e - 8), RB(RO, e), b[2], b[3]);
    }
  }
  const float head = bf_lo(lds16(kt + KT_E2 + 144)) * bf_lo(lds16(ws + WS_W5 + (lane & 7) * 2));
  mbar_wait(bar_prev, 0);
  __syncwarp();
  const uint32_t pa = ws + WS_P + (514 + 8 * g + 2 * c) * 4;
#pragma unroll
  for (int mt = 0; mt < 12; mt++)
#pragma unroll
    for (int h = 0; h < 2; h++) {
      const uint32_t a = pa + (16 * mt + 8 * h) * 32;
      float x = acc[mt][2 * h], y = acc[mt][2 * h + 1];
      if (mt >= 4 || (mt == 3 && h == 1 && g == 7)) { const float2 o = lds64f(a); x += o.x; y += o.y; }
      sts64f(a, x, y);
    }
  if (lane < 8) sts32f(ws + WS_P + (506 + lane) * 4, head);
}
__device__ __forceinline__ void conv_seg3(uint32_t ws, uint32_t u0, uint32_t kt, int lane) {
  const int g = lane >> 2, c = lane & 3;
  uint32_t RE[9], RO[9];
  load_tab9(kt + KT_E3, g, c, RE);
  load_tab9(kt + KT_O3, g, c, RO);
  const int mi = lane >> 3, lam = (lane & 7) + 8 * (mi & 1);
  const uint32_t addr = ws + (2 * (lam - 16) + (mi >> 1) + 2) * 16;
  float acc[4][2][4];
#pragma unroll
  for (int i = 0; i < 8; i++) acc[i >> 1][i & 1][0] = acc[i >> 1][i & 1][1] = acc[i >> 1][i & 1][2] = acc[i >> 1][i & 1][3] = 0.f;
#pragma unroll
  for (int k = 0; k < 5; k++) {
    uint32_t b[4], b2[4];
    ldsm4t((k == 0 && lam < 15) ? u0 - 80 : addr + WS_W9 + k * 512, b);
    ldsm4t((k == 0 && lam < 15) ? u0 - 80 : addr + WS_W7 + k * 512, b2);
#pragma unroll
    for (int mt = 0; mt < 4; mt++) {
      const int e = 16 * (mt - k + 1);
      if (e >= 0 && e <= 64) {
        mma16816(acc[mt][0], RB(RE, e), RB(RE, e + 8), RB(RE, e - 8), RB(RE, e), b[0], b[1]);
        mma16816(acc[mt][1], RB(RE, e), RB(RE, e + 8), RB(RE, e - 8), RB(RE, e), b[2], b[3]);
      }
    }
#pragma unroll
    for (int mt = 0; mt < 4; mt++) {
      const int e = 16 * (mt - k + 1);
      if (e >= 0 && e <= 64) {
        mma16816(acc[mt][0], RB(RO, e), RB(RO, e + 8), RB(RO, e - 8), RB(RO, e), b2[0], b2[1]);
        mma16816(acc[mt][1], RB(RO, e), RB(RO, e + 8), RB(RO, e - 8), RB(RO, e), b2[2], b2[3]);
      }
    }
  }
  const float head = bf_lo(lds16(kt + KT_E3 + 144)) * bf_lo(lds16(ws + WS_W5 + (lane & 7) * 2));
  __syncwarp();
  const uint32_t pa = ws + WS_P + (1024 + 16 * g + 2 * c) * 4;
#pragma unroll
  for (int mt = 0; mt < 4; mt++)
#pragma unroll
    for (int h = 0; h < 2; h++)
#pragma unroll
      for (int nt = 0; nt < 2; nt++) sts64f(pa + (16 * mt + 8 * h) * 64 + nt * 32, acc[mt][nt][2 * h], acc[mt][nt][2 * h + 1]);
  if (lane < 6) sts32f(ws + WS_P + (1018 + lane) * 4, head);
}
#undef RB
__device__ __forceinline__ void conv_seg0(uint32_t ws, uint32_t u0, uint32_t kt, uint32_t bar_prev, int mt, uint32_t dsk2, int lane) {
  const int g = lane >> 2, c = lane & 3;
  uint32_t R[33];
  {
    const uint32_t a = kt + KT_K0 + (g & 1) * 544 + (264 + (g & 1) - g + 2 * c) * 2;
#pragma unroll
    for (int k = 0; k < 33; k++) R[k] = lds32(a - 16 * k);
  }
  const int row = 16 * mt + (lane & 15);
  const uint32_t ab = u0 + (lane >> 4) * 16;
  float acc[4][4];
#pragma unroll
  for (int i = 0; i < 4; i++) acc[i][0] = acc[i][1] = acc[i][2] = acc[i][3] = 0.f;
#define RK(e) (((e) < 0 || (e) > 256) ? 0u : R[((e) < 0 || (e) > 256) ? 0 : (e) / 8])
#pragma unroll
  for (int dl = 0; dl < 9; dl++) {
    const uint32_t ra = ab + max(row - dl, -1) * 80;
#pragma unroll
    for (int ka = 0; ka < 2; ka++) {
      uint32_t a[4];
      ldsm4(ra + ka * 32, a);
#pragma unroll
      for (int nu = 0; nu < 4; nu++) {
        const int e = 32 * dl + 8 * nu - 16 * ka;
        if (e >= 0 && e <= 264) mma16816(acc[nu], a[0], a[1], a[2], a[3], RK(e), RK(e - 8));
      }
    }
  }
#undef RK
  if (mt >= 2) {
    const uint32_t kv = lds16(kt + KT_E3 + 144) ^ 0x8000u;
    const int z = g - 2 * c;
    const uint32_t f16 = ((z == 4 || z == 5) ? kv : 0u) | ((z == 5 || z == 6) ? kv << 16 : 0u);
    const uint32_t f24 = ((z == -4 || z == -3) ? kv : 0u) | ((z == -3 || z == -2) ? kv << 16 : 0u);
    uint32_t a0[4], a1[4], a2[4];
    ldsm4(ab + (row - 32) * 80, a0);
    ldsm4(ab + (row - 32) * 80 + 32, a1);
    ldsm4(ab + (row - 31) * 80, a2);
    mma16816(acc[0], a0[0], a0[1], a0[2], a0[3], f24, f16);
    mma16816(acc[1], a1[0], a1[1], a1[2], a1[3], f16, 0u);
    mma16816(acc[2], a1[0], a1[1], a1[2], a1[3], f24, f16);
    mma16816(acc[3], a2[0], a2[1], a2[2], a2[3], f16, 0u);
    mma16816(acc[1], a0[0], a0[1], a0[2], a0[3], 0u, f24);
    mma16816(acc[3], a1[0], a1[1], a1[2], a1[3], 0u, f24);
  }
  mbar_wait(bar_prev, 0);
#pragma unroll
  for (int h = 0; h < 2; h++) {
    const int j = 16 * mt + g + 8 * h;
#pragma unroll
    for (int nu = 0; nu < 4; nu++) {
      const int t = 32 * j + 8 * nu + 2 * c;
      float x = acc[nu][2 * h], y = acc[nu][2 * h + 1];
      if (t >= 250) { const float2 o = lds64f(ws + WS_P + t * 4); x += o.x; y += o.y; }
      const uint32_t uu = lds32(u0 + j * 80 + (8 * nu + 2 * c) * 2);
      sts32(ws + t * 2, as_u32(__hadd2_rn(as_bf162(pack_bf16(x, y)), __hmul2_rn(as_bf162(uu), as_bf162(dsk2)))));
    }
  }
}

__device__ __forceinline__ void kt_put1(uint32_t tb, int copy_bytes, int x0, int x, uint32_t v) {
  sts16(tb + (x0 - x) * 2, v);
  sts16(tb + copy_bytes + (x0 + 1 - x) * 2, v);
}
__device__ __forceinline__ void kt_store(uint32_t kt, int r, int col, float val, int d) {
  const uint32_t v = pack_bf16(val, 0.f) & 0xffffu;
  if (col < 8) {
    if (r != 31 || col != 7) kt_put1(kt + KT_K0, 544, 264, 8 * r + col, v);
  } else if (col < 12) {
    const int x = 2 * r + ((col - 7) >> 1);
    if (r != 31 || col != 11) sts16(kt + ((col & 1) ? KT_O1 : KT_E1) + (78 - x) * 2, v);
  } else if (col < 16) {
    kt_put1(kt + ((col & 1) ? KT_O2 : KT_E2), 160, 72, 32 * ((col - 12) >> 1) + r + (col & 1), v);
  } else if (col < 20) {
    kt_put1(kt + ((r & 1) ? KT_O3 : KT_E3), 160, 72, 16 * (col - 16) + ((r + 1) >> 1), v);
  } else if (col == 20) {
    if (r == 0) kt_put1(kt + KT_E3, 160, 72, 64, v);
  } else if (col == 21) {
    if (r == 31) kt_put1(kt + KT_K0, 544, 264, 255, v);
  } else if (col == 22) {
    if (r == 31) sts16(kt + KT_O1 + (78 - 64) * 2, v);
  }
}

__global__ void __cluster_dims__(2, 1, 1) __launch_bounds__(512, 1)
fused_kernel(const __grid_constant__ CUtensorMap tm_x, const __grid_constant__ CUtensorMap tm_w1,
             const __grid_constant__ CUtensorMap tm_hst, const __grid_constant__ CUtensorMap tm_hld,
             const __grid_constant__ CUtensorMap tm_w2, const __grid_constant__ CUtensorMap tm_aT,
             const __grid_constant__ CUtensorMap tm_out, const __grid_constant__ CUtensorMap tm_ug, const Params p) {
  extern __shared__ uint8_t smem_raw[];
  const uint32_t sraw = smem_u32(smem_raw);
  const uint32_t sb = (sraw + 1023) & ~1023u;
  uint8_t* sm = smem_raw + (sb - sraw);
  const int tid = threadIdx.x, warp = __shfl_sync(0xffffffffu, tid >> 5, 0), lane = tid & 31;
  const int cta = blockIdx.x, cl = cta >> 1, rk = cta & 1;
  const bool has1 = cl < 64;
  const int idx = cl < 64 ? (cl & 7) * 8 + (cl >> 3) : 64;
  const int sl = (idx & 3) + ((idx >> 3) & 1) * 4, tt = 2 * (((idx >> 2) & 1) + (idx >> 4) * 2) + rk;
  const int dt5 = idx % 5, T2 = 2 * (idx / 5) + rk;
  const uint32_t bar_full1 = sb + SM_MISC;
  const uint32_t bar_empty1 = bar_full1 + 24;
  const uint32_t bar_full2 = bar_empty1 + 24;
  const uint32_t bar_empty2 = bar_full2 + 56;
  const uint32_t bar_ringfree = bar_empty2 + 56;
  const uint32_t bar_at = bar_ringfree + 8;
  const uint32_t bar_gate = bar_at + 8;
  const uint32_t bar_slice = bar_gate + 8;
  const uint32_t bar_go = bar_slice + 64;
  const uint32_t bar_cvl = bar_go + 8;
  const uint32_t bar_cvc = bar_cvl + 8;
  const uint32_t bar_u = bar_cvc + 8;
  const uint32_t bar_wr = bar_u + 8;
  const uint32_t bar_seg = bar_wr + 16;
  const uint32_t peer_off = mapa(sb, rk ^ 1) - sb;
  if (tid == 0) TS(0);

  if (tid == 0) {
    for (int i = 0; i < G1_STAGES; i++) { mbar_init(bar_full1 + 8 * i, 1); mbar_init(bar_empty1 + 8 * i, 16); }
    if (has1) {
      asm volatile("fence.mbarrier_init.release.cluster;" ::: "memory");
#pragma unroll
      for (int kb = 0; kb < G1_STAGES; kb++) {
        mbar_expect_tx(bar_full1 + 8 * kb, G1_TX);
        tma_load2d(sb + SM_X + kb * 16384, &tm_x, kb * 64, tt * 128, bar_full1 + 8 * kb);
      }
    }
  }
  if (tid == 96) {
    for (int i = 0; i < G2_STAGES; i++) { mbar_init(bar_full2 + 8 * i, 1); mbar_init(bar_empty2 + 8 * i, 16); }
    mbar_init(bar_ringfree, 4);
    mbar_init(bar_at, 1);
    mbar_init(bar_gate, 8);
    for (int i = 0; i < 8; i++) mbar_init(bar_slice + 8 * i, 1);
    mbar_init(bar_go, 16);
    mbar_init(bar_cvl, NCONV_WARPS);
    mbar_init(bar_cvc, 2 * NCONV_WARPS);
    mbar_init(bar_u, 1);
    mbar_init(bar_wr, 8);
    mbar_init(bar_wr + 8, 8);
    for (int i = 0; i < 15; i++) mbar_init(bar_seg + 8 * i, 1);
    for (int i = 0; i < 6; i++) sts32(sb + SM_CTR + 4 * i, 0);
    asm volatile("fence.mbarrier_init.release.cluster;" ::: "memory");
  }
  if (tid == 32 && has1) l2_prefetch(p.w1 + (size_t)cta * 7680, 15360);
  if (tid == 64) { prefetch_tmap(&tm_w1); prefetch_tmap(&tm_ug); prefetch_tmap(&tm_hst); prefetch_tmap(&tm_hld); prefetch_tmap(&tm_w2); prefetch_tmap(&tm_aT); prefetch_tmap(&tm_out); }
  if (tid >= 128 && tid < 128 + 96 && has1) ((uint32_t*)(sm + SM_B1))[tid - 128] = ((const uint32_t*)(p.b1 + sl * 192))[tid - 128];
  cluster_arrive();
  const unsigned epoch = g_epoch[cta];
  cluster_wait();

  const int wg = warp >> 2, w4 = warp & 3, g = lane >> 2, c = lane & 3;
  if (has1) {
    if (warp < 8) {
      if (tid == 0) {
#pragma unroll
        for (int kb = 0; kb < G1_STAGES; kb++)
          tma_load3d_mc(sb + SM_W + kb * 24576 + rk * 12288, &tm_w1, 0, kb * 64 + rk * 32, sl * 3, bar_full1 + 8 * kb);
      }
      float acc[96];
#pragma unroll
      for (int i = 0; i < 96; i++) acc[i] = 0.f;
      {
        const uint64_t da0 = make_desc(sb + SM_X + wg * 8192, 16, 1024, 1);
        const uint64_t db0 = make_desc(sb + SM_W, 4096, 1024, 1);
        const uint32_t rel = bar_empty1 + (lane ? peer_off : 0u);
        uint32_t so = 0, ph = 0, prev = 0, pph = 0;
#pragma unroll 1
        for (int kb = 0; kb < 10; kb++) {
          mbar_wait(bar_full1 + so * 8, ph);
          if (tid == 0 && kb == 0) TS(1);
          const uint64_t da = da0 + so * (16384 >> 4), db = db0 + so * (24576 >> 4);
          wg_fence();
#pragma unroll
          for (int k = 0; k < 4; k++) wgmma_n192(acc, da + k * 2, db + (k >> 1) * 768 + (k & 1) * 128);
          wg_commit();
          const uint32_t cur = so, cph = ph;
          if (++so == G1_STAGES) { so = 0; ph ^= 1; }
          if (kb > 0 && kb + 2 < 10) {
            wg_wait<1>();
            if (lane < 2) mbar_arrive_cluster(rel + prev * 8);
            if (tid == (kb & 1) * 128) {
              mbar_wait(bar_empty1 + 8 * prev, pph);
              mbar_expect_tx(bar_full1 + 8 * prev, G1_TX);
              tma_load2d(sb + SM_X + prev * 16384, &tm_x, (kb + 2) * 64, tt * 128, bar_full1 + 8 * prev);
              tma_load3d_mc(sb + SM_W + prev * 24576 + rk * 12288, &tm_w1, 0, (kb + 2) * 64 + rk * 32, sl * 3, bar_full1 + 8 * prev);
              if (kb == 3) l2_prefetch(p.w2 + (size_t)cta * 7680, 15360);
            }
            __syncwarp();
          }
          prev = cur; pph = cph;
        }
      }
      wg_wait<0>();
      if (lane == 0) mbar_arrive(bar_go);
      if (tid == 0) TS(3);
      const uint32_t* b1s = (const uint32_t*)(sm + SM_B1);
      const int mrow = w4 * 16 + (lane & 7) + ((lane >> 3) & 1) * 8;
      const bf162 zero2 = __float2bfloat162_rn(0.f);
      named_bar(1 + wg, 128);
#pragma unroll
      for (int j = 0; j < 24; j += 2) {
        uint32_t r[4];
#pragma unroll
        for (int q = 0; q < 4; q++) {
          const int jj = j + (q >> 1);
          bf162 v = as_bf162(pack_bf16(acc[4 * jj + 2 * (q & 1)], acc[4 * jj + 2 * (q & 1) + 1]));
          v = __hadd2_rn(v, as_bf162(b1s[jj * 4 + c]));
          v = __hmax2(v, zero2);
          v = __hmul2_rn(v, v);
          r[q] = as_u32(v);
        }
        const int jl = j + (lane >> 4);
        const int box = jl >> 3, chunk = jl & 7;
        stsm_x4(sb + SM_X + box * 16384 + wg * 8192 + mrow * 128 + ((chunk ^ (mrow & 7)) << 4), r[0], r[1], r[2], r[3]);
      }
      fence_async_smem();
      named_bar(1 + wg, 128);
      if ((tid & 127) == 0) {
#pragma unroll
        for (int b = 0; b < 3; b++)
          tma_store2d(&tm_hst, sb + SM_X + b * 16384 + wg * 8192, 0, (sl * 3 + b) * L_ + tt * 128 + wg * 64);
        if (wg == 0) {
          mbar_wait(bar_gate, 0);
          bulk_store(g_gate + tt * 128 + sl * 16, sb + SM_GOUT, 32);
        }
        bulk_commit();
        if (tid == 0) TS(4);
        bulk_wait_read0();
        mbar_arrive_cluster(bar_ringfree);
        mbar_arrive_cluster(bar_ringfree + peer_off);
        bulk_wait0();
        if (tid == 0) TS(5);
        red_relaxed_add(&g_hflag[(tt * 8 + sl) * 8], 1);
      }
      __syncwarp();
    } else {
      const int wgs = wg & 1, t128 = tid & 127;
      const int uo = (5 * cta) & 7;
      if (tid == 384) {
        mbar_expect_tx(bar_u, uo > 3 ? 32768 : 16384);
#pragma unroll
        for (int i = 0; i < 4; i++) {
          tma_load2d(sb + SM_USTG + i * 4096, &tm_ug, 5 * cta - uo, i * 256, bar_u);
          if (uo > 3) tma_load2d(sb + SM_USTG + 16384 + i * 4096, &tm_ug, 5 * cta - uo + 8, i * 256, bar_u);
        }
      }
      for (int i = t128; i < (wgs ? 2 : 3) * (KT_BYTES / 16); i += 128) {
        const int chz = i / (KT_BYTES / 16);
        sts128u(sb + SM_KT + (wgs ? 2 + chz : (chz == 2 ? 4 : chz)) * KT_BYTES + (i % (KT_BYTES / 16)) * 16, 0, 0, 0, 0);
      }
      if (wgs && t128 < 25) sts128u(sb + SM_U0 + (t128 / 5) * U0_BYTES + (t128 % 5) * 16, 0, 0, 0, 0);
      {
        const int t = tt * 128 + sl * 16 + (warp - 8) * 2;
        const uint32_t* xr = (const uint32_t*)(p.u + (size_t)t * D_);
        const uint32_t* gw = (const uint32_t*)p.gate_w;
        uint32_t xv[20], gv[10];
#pragma unroll
        for (int i = 0; i < 20; i++) xv[i] = __ldg(xr + lane + 32 * i);
#pragma unroll
        for (int i = 0; i < 10; i++) gv[i] = __ldg(gw + lane + 32 * i);
        float s0 = 0.f, s1 = 0.f;
#pragma unroll
        for (int i = 0; i < 10; i++) {
          const bf162 v0 = __hmul2_rn(as_bf162(xv[i]), as_bf162(gv[i])), v1 = __hmul2_rn(as_bf162(xv[i + 10]), as_bf162(gv[i]));
          s0 += __low2float(v0) + __high2float(v0);
          s1 += __low2float(v1) + __high2float(v1);
        }
#pragma unroll
        for (int o = 16; o; o >>= 1) { s0 += __shfl_xor_sync(0xffffffffu, s0, o); s1 += __shfl_xor_sync(0xffffffffu, s1, o); }
        if (lane < 2) {
          const float z = __bfloat162float(__float2bfloat16_rn(lane ? s1 : s0));
          ((bf16*)(sm + SM_GOUT))[(warp - 8) * 2 + lane] = __float2bfloat16_rn(1.f / (1.f + __expf(-z)));
          fence_async_smem();
        }
        __syncwarp();
        if (lane == 0) mbar_arrive(bar_gate);
      }
      if (tid == 256) TS(14);
      const uint32_t kgB = sb + SM_KG + wgs * KG_BYTES, kgT = kgB + KG_T;
#pragma unroll 1
      for (int job = wgs; job < 3; job += 2) {
        const int nch = job == 2 ? 3 : 6;
        const int gam = w4 & 1, role = w4 >> 1;
        const int dB = 5 * cta + (job == 2 ? 4 : 2 * job + gam);
        const int po = dB * NM_ + (job == 2 ? 96 * gam : 0) + lane;
        const float dt = __bfloat162float(__float2bfloat16_rn(expf(ldbf(p.logdt + dB))));
        float pr[6];
        pr[0] = ldbf(p.Are + po); pr[1] = ldbf(p.Aim + po); pr[2] = ldbf(p.Bre + po);
        pr[3] = ldbf(p.Bim + po); pr[4] = ldbf(p.Cre + po); pr[5] = ldbf(p.Cim + po);
        float acc[24];
#pragma unroll
        for (int i = 0; i < 24; i++) acc[i] = 0.f;
        const uint32_t bst = kgB + gam * 3456 + (lane >> 2) * 144 + (lane & 3) * 4;
        const uint32_t tst = kgT + (gam * 32 + lane) * 96;
        const uint32_t tld = kgT + ((w4 >> 1) * 32 + c) * 96;
        const uint64_t db0 = make_desc(kgB, 144, 1152, 0);
#pragma unroll 1
        for (int k = 0; k < nch; k++) {
          const float ar2 = dt * pr[0] * 1.4426950409f, ai = dt * pr[1];
          const float fh = ai * 0.15915494f, fl = fmaf(ai, 6.4206382e-9f, fmaf(ai, 0.15915494f, -fh));
          const float2 cc = cmul(make_float2(pr[4], pr[5]), make_float2(dt * pr[2], dt * pr[3]));
          if (k + 1 < nch) {
            const int o = po + 32 * (k + 1);
            pr[0] = ldbf(p.Are + o); pr[1] = ldbf(p.Aim + o); pr[2] = ldbf(p.Bre + o);
            pr[3] = ldbf(p.Bim + o); pr[4] = ldbf(p.Cre + o); pr[5] = ldbf(p.Cim + o);
          }
          if (role == 0) {
            const float2 e1 = cexp_p2(ar2, fh, fl, 1.f), e8 = cexp_p2(ar2, fh, fl, 8.f);
            const float2 e2 = csqr(e1), e3 = cmul(e2, e1), e4 = csqr(e2), e5 = cmul(e4, e1), e6 = csqr(e3), e7 = cmul(e4, e3);
            const float2 g2 = csqr(e8), g3 = cmul(g2, e8), g4 = csqr(g2), g5 = cmul(g4, e8), g6 = csqr(g3), g7 = cmul(g4, g3);
            const uint32_t v0 = packB(cc), v1 = packB(cmul(cc, e1)), v2 = packB(cmul(cc, e2)), v3 = packB(cmul(cc, e3)),
                           v4 = packB(cmul(cc, e4)), v5 = packB(cmul(cc, e5)), v6 = packB(cmul(cc, e6)), v7 = packB(cmul(cc, e7)),
                           v21 = packB(cmul(cc, csub(e7, e8)));
            wg_wait<0>();
            named_bar(3 + wgs, 128);
            sts32(bst, v0); sts32(bst + 16, v1); sts32(bst + 32, v2); sts32(bst + 48, v3);
            sts32(bst + 64, v4); sts32(bst + 80, v5); sts32(bst + 96, v6); sts32(bst + 112, v7);
            sts32(bst + 2304 + 80, v21);
            sts128f(tst, 1.f, 0.f, e8.x, e8.y); sts128f(tst + 16, g2.x, g2.y, g3.x, g3.y);
            sts128f(tst + 32, g4.x, g4.y, g5.x, g5.y); sts128f(tst + 48, g6.x, g6.y, g7.x, g7.y);
          } else {
            const float2 e2 = cexp_p2(ar2, fh, fl, 2.f), f1 = cexp_p2(ar2, fh, fl, 64.f);
            const float2 h1 = cexp_p2(ar2, fh, fl, 256.f), h4 = cexp_p2(ar2, fh, fl, 1024.f);
            const float2 e4 = csqr(e2), e6 = cmul(e4, e2), e8 = csqr(e4);
            const float2 f2 = csqr(f1), f3 = cmul(f2, f1), h2 = csqr(h1), h3 = cmul(h2, h1);
            const float2 c1 = cmul(cc, h1), c2 = cmul(cc, h2), c3 = cmul(cc, h3), c4 = cmul(cc, h4);
            const uint32_t v8 = packB(c1), v9 = packB(cmul(c1, e2)), v10 = packB(cmul(c1, e4)), v11 = packB(cmul(c1, e6)),
                           v12 = packB(c2), v13 = packB(cmul(c2, e4)), v14 = packB(c3), v15 = packB(cmul(c3, e4)),
                           v16 = packB(c4), v17 = packB(cmul(c4, h1)), v18 = packB(cmul(c4, h2)), v19 = packB(cmul(c4, h3)),
                           v20 = packB(cmul(c4, h4)), v22 = packB(cmul(c1, csub(e6, e8)));
            wg_wait<0>();
            named_bar(3 + wgs, 128);
            const uint32_t b1a = bst + 1152, b2a = bst + 2304;
            sts32(b1a, v8); sts32(b1a + 16, v9); sts32(b1a + 32, v10); sts32(b1a + 48, v11);
            sts32(b1a + 64, v12); sts32(b1a + 80, v13); sts32(b1a + 96, v14); sts32(b1a + 112, v15);
            sts32(b2a, v16); sts32(b2a + 16, v17); sts32(b2a + 32, v18); sts32(b2a + 48, v19);
            sts32(b2a + 64, v20); sts32(b2a + 96, v22);
            sts128f(tst + 64, 1.f, 0.f, f1.x, f1.y); sts128f(tst + 80, f2.x, f2.y, f3.x, f3.y);
          }
          fence_async_smem();
          named_bar(3 + wgs, 128);
          uint32_t a[4][4];
#pragma unroll
          for (int ks = 0; ks < 4; ks++)
#pragma unroll
            for (int hf = 0; hf < 2; hf++) {
              const uint32_t ta = tld + (8 * ks + 4 * hf) * 96;
              const float2 G = lds64f(ta + g * 8);
              const float4 F = lds128f(ta + 64 + (w4 & 1) * 16);
              const float2 q0 = cmul(G, make_float2(F.x, F.y)), q1 = cmul(G, make_float2(F.z, F.w));
              a[ks][2 * hf] = pack_bf16(q0.x, q0.y);
              a[ks][2 * hf + 1] = pack_bf16(q1.x, q1.y);
            }
          wg_fence();
#pragma unroll
          for (int ks = 0; ks < 4; ks++) wgmma_n48_rs(acc, a[ks], db0 + ks * 18);
          wg_commit();
        }
        wg_wait<0>();
        float kv[12];
#pragma unroll
        for (int i = 0; i < 12; i++) kv[i] = (w4 >> 1) ? acc[12 + i] : acc[i];
        bool wr = true;
        if (job == 2) {
          named_bar(3 + wgs, 128);
          const uint32_t xa = kgT + ((w4 & 1) * 32 + lane) * 48;
          if (w4 >> 1) {
            sts128f(xa, kv[0], kv[1], kv[2], kv[3]); sts128f(xa + 16, kv[4], kv[5], kv[6], kv[7]); sts128f(xa + 32, kv[8], kv[9], kv[10], kv[11]);
          }
          named_bar(3 + wgs, 128);
          wr = (w4 >> 1) == 0;
          if (wr) {
#pragma unroll
            for (int i = 0; i < 3; i++) {
              const float4 o = lds128f(xa + 16 * i);
              kv[4 * i] += o.x; kv[4 * i + 1] += o.y; kv[4 * i + 2] += o.z; kv[4 * i + 3] += o.w;
            }
          }
        }
        if (wr) {
          const int chl = job == 2 ? 4 : 2 * job + (w4 >> 1);
          const uint32_t kt = sb + SM_KT + chl * KT_BYTES;
#pragma unroll
          for (int i = 0; i < 12; i++)
            kt_store(kt, 16 * (w4 & 1) + g + 8 * ((i >> 1) & 1), 8 * (i >> 2) + 2 * c + (i & 1), kv[i], 5 * cta + chl);
        }
        if (tid == 256) TS(15 + (job >> 1));
      }
      if (wgs) {
#pragma unroll 1
        for (int rnd = 0; rnd < 2; rnd++) {
          mbar_wait(bar_u, rnd);
          if (tid == 384) TS(17);
#pragma unroll 1
          for (int bx = 0; bx < (uo > 3 ? 2 : 1); bx++) {
            const int chl = g + 8 * bx - uo;
#pragma unroll 4
            for (int i = 0; i < 8; i++) {
              const int t0 = (w4 * 8 + i) * 32;
              uint32_t r[4];
              ldsm4t(sb + SM_USTG + bx * 16384 + (t0 + lane) * 16, r);
              if (chl >= 0 && chl < 5) {
                const uint32_t o = sb + SM_U0 + chl * U0_BYTES + 80 + (rnd * 32 + (t0 >> 5)) * 80 + c * 4;
                sts32(o, r[0]); sts32(o + 16, r[1]); sts32(o + 32, r[2]); sts32(o + 48, r[3]);
              }
            }
          }
          named_bar(4, 128);
          if (rnd == 0 && tid == 384) {
            mbar_expect_tx(bar_u, uo > 3 ? 32768 : 16384);
#pragma unroll
            for (int i = 0; i < 4; i++) {
              tma_load2d(sb + SM_USTG + i * 4096, &tm_ug, 5 * cta - uo, 1024 + i * 256, bar_u);
              if (uo > 3) tma_load2d(sb + SM_USTG + 16384 + i * 4096, &tm_ug, 5 * cta - uo + 8, 1024 + i * 256, bar_u);
            }
          }
        }
#pragma unroll 1
        for (int i = 0; i < 4; i++)
          build_w(sb + SM_WS + (i >> 1) * WS_BYTES, sb + SM_U0 + (i >> 1) * U0_BYTES + 80, (i & 1) * 128 + t128 - 2);
        if (tid == 384) TS(18);
      }
      named_bar(5, 256);
      build_w(sb + SM_WS + 2 * WS_BYTES, sb + SM_U0 + 2 * U0_BYTES + 80, (tid - 256) - 2);
      __syncwarp();
      if (lane == 0) mbar_arrive(bar_go);
      if (tid == 256) TS(19);
    }
    if (warp < NCONV_WARPS) {
      mbar_wait(bar_go, 0);
      if (tid == 256) TS(20);
      uint32_t stored = 0;
#pragma unroll 1
      for (;;) {
        uint32_t it = 0;
        if (lane == 0) asm volatile("atom.relaxed.cta.shared.add.u32 %0, [%1], 1;" : "=r"(it) : "r"(sb + SM_CTR) : "memory");
        it = __shfl_sync(0xffffffffu, it, 0);
        if (it >= 51) break;
        if (lane == 0) TR(it);
        if (it >= 6 && it < 22) {
          const int ch = 3 + ((it - 6) >> 3);
          build_w(sb + SM_WSHI + (ch - 3) * WS_BYTES, sb + SM_U0 + ch * U0_BYTES + 80, ((it - 6) & 7) * 29 + lane - 2 + (lane >= 29 ? 1000 : 0));
          __syncwarp();
          if (lane == 0) mbar_arrive(bar_wr + (ch - 3) * 8);
        } else {
          const int k = it < 6 ? it : it - 16;
          const int ch = k < 15 ? k / 3 : (k - 15) >> 2;
          const uint32_t ws = sb + (ch < 3 ? SM_WS + ch * WS_BYTES : SM_WSHI + (ch - 3) * WS_BYTES);
          const uint32_t u0 = sb + SM_U0 + ch * U0_BYTES + 80, kt = sb + SM_KT + ch * KT_BYTES, bs = bar_seg + ch * 24;
          if (k < 15) {
            const int ty = k - 3 * ch;
            if (ch >= 3) mbar_wait(bar_wr + (ch - 3) * 8, 0);
            if (ty == 0) conv_seg3(ws, u0, kt, lane);
            else if (ty == 1) conv_seg2(ws, u0, kt, bs, lane);
            else conv_seg1(ws, u0, kt, bs + 8, lane);
            __syncwarp();
            if (lane == 0) mbar_arrive(bs + ty * 8);
          } else {
            const uint32_t dk = __ldg((const unsigned short*)p.Dsk + 5 * cta + ch);
            conv_seg0(ws, u0, kt, bs + 16, 3 - ((k - 15) & 3), dk | (dk << 16), lane);
            fence_async_smem();
            __syncwarp();
            if (lane == 0) {
              uint32_t n;
              asm volatile("atom.acq_rel.cta.shared.add.u32 %0, [%1], 1;" : "=r"(n) : "r"(sb + SM_CTR + 4 + 4 * ch) : "memory");
              if (n == 3) {
                bulk_store(g_aT + (size_t)(5 * cta + ch) * L_, ws, 4096);
                bulk_commit();
                stored |= 1u << ch;
              }
            }
          }
        }
        if (lane == 0) TR(64 + it);
      }
      if (lane == 0) {
        if (stored) bulk_wait_read0();
        mbar_arrive(bar_cvl);
        mbar_arrive_cluster(bar_cvc);
        mbar_arrive_cluster(bar_cvc + peer_off);
        if (stored) {
          bulk_wait0();
          for (int ch = 0; ch < 5; ch++)
            if (stored >> ch & 1) red_relaxed_add(&g_aflag[((5 * cta + ch) >> 7) * 32], 1);
        }
      }
      __syncwarp();
    }
  }
  if (warp < 8) {
    float acc[40];
#pragma unroll
    for (int i = 0; i < 40; i++) acc[i] = 0.f;
    const int d0 = dt5 * 128 + wg * 64 + w4 * 16 + g;
    const bf162 b2a = __bfloat162bfloat162(p.b2[d0]), b2b = __bfloat162bfloat162(p.b2[d0 + 8]);
    if (has1) mbar_wait(bar_cvl, 0);
    if (tid == 0) TS(21);
    {
      const uint64_t da0 = make_desc(sb + wg * 8192, 16, 1024, 1);
      const uint64_t db0 = make_desc(sb + 16384, 16, 1024, 1);
      const uint32_t rel = bar_empty2 + (lane ? peer_off : 0u);
      uint32_t so = 0, ph = 0, prev = 0;
#pragma unroll 1
      for (int kb = 0; kb < 24; kb++) {
        mbar_wait(bar_full2 + so * 8, ph);
        if (tid == 0 && kb == 0) TS(7);
        if (tid == 0 && kb == 12) TS(8);
        const uint64_t da = da0 + so * (G2_STAGE_BYTES >> 4), db = db0 + so * (G2_STAGE_BYTES >> 4);
        wg_fence();
#pragma unroll
        for (int k = 0; k < 4; k++) wgmma_n80(acc, da + k * 128, db + k * 2);
        wg_commit();
        const uint32_t cur = so;
        if (++so == G2_STAGES) { so = 0; ph ^= 1; }
        if (kb > 0 && kb - 1 + G2_STAGES < 24) {
          wg_wait<1>();
          if (lane < 2) mbar_arrive_cluster(rel + prev * 8);
        }
        prev = cur;
      }
    }
    wg_wait<0>();
    if (tid == 0) TS(9);
    mbar_wait(bar_at, 0);
    const uint32_t* gs = (const uint32_t*)(sm + SM_GATE);
    const bf162 one2 = __float2bfloat162_rn(1.f);
#pragma unroll
    for (int j = 0; j < 10; j += 2) {
      uint32_t a[4], r[4];
      ldsm_x4(sb + SM_AT + (wg * 64 + w4 * 16 + (lane & 15)) * 160 + (j + (lane >> 4)) * 16, a[0], a[1], a[2], a[3]);
#pragma unroll
      for (int q = 0; q < 4; q++) {
        const int jj = j + (q >> 1);
        const bf162 gg = as_bf162(gs[jj * 4 + c]);
        bf162 v = as_bf162(pack_bf16(acc[4 * jj + 2 * (q & 1)], acc[4 * jj + 2 * (q & 1) + 1]));
        v = __hadd2_rn(v, (q & 1) ? b2b : b2a);
        v = __hmul2_rn(v, __hsub2_rn(one2, gg));
        r[q] = as_u32(__hadd2_rn(__hmul2_rn(as_bf162(a[q]), gg), v));
      }
      const int tr = 8 * (j + (lane >> 4)) + (lane & 7);
      const int chunk = 2 * w4 + ((lane >> 3) & 1);
      stsm_x4_t(sb + SM_OUT + wg * 10240 + tr * 128 + ((chunk ^ (tr & 7)) << 4), r[0], r[1], r[2], r[3]);
    }
    fence_async_smem();
    named_bar(1 + wg, 128);
    if ((tid & 127) == 0) {
      tma_store2d(&tm_out, sb + SM_OUT + wg * 10240, dt5 * 128 + wg * 64, T2 * 80);
      bulk_commit();
      bulk_wait_read0();
      if (tid == 0) TS(10);
    }
  } else if (warp == 14) {
    if (lane == 0) {
      if (has1) mbar_wait(bar_ringfree, 0);
      const int c0 = dt5 * 128 + rk * 64, r0 = T2 * 80;
      const uint32_t dst = sb + rk * 8192;
#pragma unroll
      for (int kb = 0; kb < G2_EARLY; kb++) {
        mbar_expect_tx(bar_full2 + 8 * kb, G2_STAGE_BYTES);
        tma_load2d_mc(dst + kb * G2_STAGE_BYTES, &tm_w2, c0, kb * 64, bar_full2 + 8 * kb);
      }
#pragma unroll
      for (int kb = 0; kb < 24; kb++) {
        const int s = kb % G2_STAGES;
        if (kb == G2_EARLY) {
          if (has1) mbar_wait(bar_cvc, 0);
#pragma unroll
          for (int k2 = G2_EARLY; k2 < G2_STAGES; k2++) {
            mbar_expect_tx(bar_full2 + 8 * k2, G2_STAGE_BYTES);
            tma_load2d_mc(dst + k2 * G2_STAGE_BYTES, &tm_w2, c0, k2 * 64, bar_full2 + 8 * k2);
          }
        }
        if (kb >= G2_STAGES) {
          mbar_wait(bar_empty2 + 8 * s, ((kb / G2_STAGES) - 1) & 1);
          mbar_expect_tx(bar_full2 + 8 * s, G2_STAGE_BYTES);
          tma_load2d_mc(dst + s * G2_STAGE_BYTES, &tm_w2, c0, kb * 64, bar_full2 + 8 * s);
        }
        if (kb % 3 == 0) mbar_wait(bar_slice + 8 * (kb / 3), 0);
        tma_load2d(sb + s * G2_STAGE_BYTES + 16384, &tm_hld, 0, kb * L_ + r0, bar_full2 + 8 * s);
      }
      g_epoch[cta] = epoch + 1;
    }
  } else if (warp == 15) {
    const int r0 = T2 * 80;
    const int t0 = r0 >> 7, t1 = min(15, (r0 + 79) >> 7);
    const unsigned* fl = &g_hflag[(((lane & 8) ? t1 : t0) * 8 + (lane & 7)) * 8];
    const unsigned target = (epoch + 1) * 2;
    if (has1) mbar_wait(bar_ringfree, 0);
    unsigned done = 0;
#pragma unroll 1
    for (int it = 0; done != 0xffu; ++it) {
      const unsigned rdy = __ballot_sync(0xffffffffu, (int)(ld_relaxed(fl) - target) >= 0);
      const unsigned both = rdy & (rdy >> 8) & 0xffu;
      if (lane < 8 && ((both & ~done) >> lane & 1)) mbar_arrive(bar_slice + 8 * lane);
      done = both;
      if (it > SPIN_LIMIT) SPIN_FAIL;
    }
    if (lane == 0) TS(6);
    for (int i = lane; i < 40; i += 32) {
      const int t = r0 + 2 * i;
      ((uint32_t*)(sm + SM_GATE))[i] = t < L_ ? __ldcg((const uint32_t*)(g_gate + t)) : 0u;
    }
    __syncwarp();
    if (lane == 0) {
      if (has1) mbar_wait(bar_cvl, 0);
      const unsigned ta = (epoch + 1) * 128;
#pragma unroll 1
      for (int it = 0; (int)(ld_relaxed(&g_aflag[dt5 * 32]) - ta) < 0; ++it) {
        __nanosleep(100);
        if (it > SPIN_LIMIT) SPIN_FAIL;
      }
      TS(22);
      mbar_expect_tx(bar_at, 20480);
      tma_load2d(sb + SM_AT, &tm_aT, r0, dt5 * 128, bar_at);
    }
  }
}

typedef CUresult (*EncodeFn)(CUtensorMap*, CUtensorMapDataType, cuuint32_t, void*, const cuuint64_t*, const cuuint64_t*,
                             const cuuint32_t*, const cuuint32_t*, CUtensorMapInterleave, CUtensorMapSwizzle,
                             CUtensorMapL2promotion, CUtensorMapFloatOOBfill);

static void make_map(EncodeFn fn, CUtensorMap* m, const void* ptr, uint64_t inner, uint64_t outer, uint32_t box_in, uint32_t box_out,
                     CUtensorMapSwizzle swz) {
  cuuint64_t dims[2] = {inner, outer};
  cuuint64_t strides[1] = {inner * 2};
  cuuint32_t box[2] = {box_in, box_out};
  cuuint32_t es[2] = {1, 1};
  CUresult r = fn(m, CU_TENSOR_MAP_DATA_TYPE_BFLOAT16, 2, const_cast<void*>(ptr), dims, strides, box, es, CU_TENSOR_MAP_INTERLEAVE_NONE, swz,
     CU_TENSOR_MAP_L2_PROMOTION_L2_256B, CU_TENSOR_MAP_FLOAT_OOB_FILL_NONE);
  (void)r;
}

extern "C" void kernel_launch(void* const* d_in, const int* in_sizes, int n_in, void* d_out, int out_size) {
  static EncodeFn fn = nullptr;
  static CUtensorMap tm_x, tm_w1, tm_hst, tm_hld, tm_w2, tm_aT, tm_out, tm_ug;
  static const void *c_x = nullptr, *c_w1 = nullptr, *c_w2 = nullptr, *c_out = nullptr;
  if (!fn) {
    void* f = nullptr;
    cudaDriverEntryPointQueryResult qr;
    cudaGetDriverEntryPoint("cuTensorMapEncodeTiled", &f, cudaEnableDefault, &qr);
    fn = (EncodeFn)f;
    cudaFuncSetAttribute(fused_kernel, cudaFuncAttributeMaxDynamicSharedMemorySize, SMEM_BYTES);
    void *ph, *pa;
    cudaGetSymbolAddress(&ph, g_h);
    cudaGetSymbolAddress(&pa, g_aT);
    make_map(fn, &tm_hst, ph, 64, 24 * L_, 64, 64, CU_TENSOR_MAP_SWIZZLE_128B);
    make_map(fn, &tm_hld, ph, 64, 24 * L_, 64, 80, CU_TENSOR_MAP_SWIZZLE_128B);
    make_map(fn, &tm_aT, pa, L_, D_, 80, 128, CU_TENSOR_MAP_SWIZZLE_NONE);
  }
  if (c_x != d_in[0]) {
    make_map(fn, &tm_x, d_in[0], D_, L_, 64, 128, CU_TENSOR_MAP_SWIZZLE_128B);
    make_map(fn, &tm_ug, d_in[0], D_, L_, 8, 256, CU_TENSOR_MAP_SWIZZLE_NONE);
    c_x = d_in[0];
  }
  if (c_w1 != d_in[10]) {
    cuuint64_t dims[3] = {64, (cuuint64_t)D_, 24};
    cuuint64_t strides[2] = {(cuuint64_t)F_ * 2, 128};
    cuuint32_t box[3] = {64, 32, 3};
    cuuint32_t es[3] = {1, 1, 1};
    fn(&tm_w1, CU_TENSOR_MAP_DATA_TYPE_BFLOAT16, 3, d_in[10], dims, strides, box, es, CU_TENSOR_MAP_INTERLEAVE_NONE,
       CU_TENSOR_MAP_SWIZZLE_128B, CU_TENSOR_MAP_L2_PROMOTION_L2_256B, CU_TENSOR_MAP_FLOAT_OOB_FILL_NONE);
    c_w1 = d_in[10];
  }
  if (c_w2 != d_in[12]) { make_map(fn, &tm_w2, d_in[12], D_, F_, 64, 64, CU_TENSOR_MAP_SWIZZLE_128B); c_w2 = d_in[12]; }
  if (c_out != d_out) { make_map(fn, &tm_out, d_out, D_, L_, 64, 80, CU_TENSOR_MAP_SWIZZLE_128B); c_out = d_out; }
  Params p;
  p.u = (const bf16*)d_in[0];
  p.Are = (const bf16*)d_in[1];
  p.Aim = (const bf16*)d_in[2];
  p.Bre = (const bf16*)d_in[3];
  p.Bim = (const bf16*)d_in[4];
  p.Cre = (const bf16*)d_in[5];
  p.Cim = (const bf16*)d_in[6];
  p.logdt = (const bf16*)d_in[7];
  p.Dsk = (const bf16*)d_in[8];
  p.w1 = (const bf16*)d_in[10];
  p.b1 = (const bf16*)d_in[11];
  p.w2 = (const bf16*)d_in[12];
  p.b2 = (const bf16*)d_in[13];
  p.gate_w = (const bf16*)d_in[14];
  fused_kernel<<<NCTA, 512, SMEM_BYTES, cudaStreamPerThread>>>(tm_x, tm_w1, tm_hst, tm_hld, tm_w2, tm_aT, tm_out, tm_ug, p);
}
```

```cpp
#include <cuda_runtime.h>
#include <cuda_bf16.h>
#include <cuda.h>
#include <stdint.h>
#include <string.h>

typedef __nv_bfloat16 bf16;
typedef __nv_bfloat162 bf162;

constexpr int L_ = 2048, D_ = 640, NM_ = 192, F_ = 1536;
constexpr int NCTA = 130;

__device__ bf16 g_h[L_ * F_];
__device__ bf16 g_aT[D_ * L_];
__device__ __align__(16) bf16 g_gate[L_ + 64];
__device__ unsigned g_hflag[128 * 2 * 8];
__device__ unsigned g_aflag[8 * 32];
__device__ unsigned g_epoch[NCTA];
__device__ unsigned g_err;
#define TS(i)
#define TR(i)

#define SPIN_LIMIT 2000000
#define SPIN_FAIL __trap()
__device__ __forceinline__ uint32_t smem_u32(const void* p) { return (uint32_t)__cvta_generic_to_shared(p); }
__device__ __forceinline__ void mbar_init(uint32_t bar, uint32_t cnt) {
  asm volatile("mbarrier.init.shared::cta.b64 [%0], %1;" ::"r"(bar), "r"(cnt) : "memory");
}
__device__ __forceinline__ void mbar_arrive(uint32_t bar) {
  asm volatile("mbarrier.arrive.shared::cta.b64 _, [%0];" ::"r"(bar) : "memory");
}
__device__ __forceinline__ void mbar_expect_tx(uint32_t bar, uint32_t bytes) {
  asm volatile("mbarrier.arrive.expect_tx.shared::cta.b64 _, [%0], %1;" ::"r"(bar), "r"(bytes) : "memory");
}
__device__ __forceinline__ void mbar_wait(uint32_t bar, uint32_t parity) {
  asm volatile(
      "{\n.reg .pred p;\n.reg .u32 c;\nmov.u32 c, 0;\n"
      "WL:\nmbarrier.try_wait.parity.shared::cta.b64 p, [%0], %1;\n@p bra WD;\n"
      "add.u32 c, c, 1;\nsetp.lt.u32 p, c, 4000000;\n@p bra WL;\ntrap;\nWD:\n}"
      ::"r"(bar), "r"(parity) : "memory");
}
__device__ __forceinline__ void tma_load2d(uint32_t dst, const CUtensorMap* tm, int c0, int c1, uint32_t bar) {
  asm volatile("cp.async.bulk.tensor.2d.shared::cluster.global.mbarrier::complete_tx::bytes [%0], [%1, {%3, %4}], [%2];"
               ::"r"(dst), "l"(tm), "r"(bar), "r"(c0), "r"(c1) : "memory");
}
__device__ __forceinline__ void tma_load2d_mc(uint32_t dst, const CUtensorMap* tm, int c0, int c1, uint32_t bar) {
  asm volatile("cp.async.bulk.tensor.2d.shared::cluster.global.mbarrier::complete_tx::bytes.multicast::cluster [%0], [%1, {%3, %4}], [%2], %5;"
               ::"r"(dst), "l"(tm), "r"(bar), "r"(c0), "r"(c1), "h"((uint16_t)3) : "memory");
}
__device__ __forceinline__ void tma_load3d_mc(uint32_t dst, const CUtensorMap* tm, int c0, int c1, int c2, uint32_t bar) {
  asm volatile("cp.async.bulk.tensor.3d.shared::cluster.global.mbarrier::complete_tx::bytes.multicast::cluster [%0], [%1, {%3, %4, %5}], [%2], %6;"
               ::"r"(dst), "l"(tm), "r"(bar), "r"(c0), "r"(c1), "r"(c2), "h"((uint16_t)3) : "memory");
}
__device__ __forceinline__ void tma_pf2d(const CUtensorMap* tm, int c0, int c1) {
  asm volatile("cp.async.bulk.prefetch.tensor.2d.L2.global [%0, {%1, %2}];" ::"l"(tm), "r"(c0), "r"(c1) : "memory");
}
__device__ __forceinline__ void tma_pf3d(const CUtensorMap* tm, int c0, int c1, int c2) {
  asm volatile("cp.async.bulk.prefetch.tensor.3d.L2.global [%0, {%1, %2, %3}];" ::"l"(tm), "r"(c0), "r"(c1), "r"(c2) : "memory");
}
__device__ __forceinline__ void l2_prefetch(const void* p, uint32_t bytes) {
  asm volatile("cp.async.bulk.prefetch.L2.global [%0], %1;" ::"l"(p), "r"(bytes) : "memory");
}
__device__ __forceinline__ void prefetch_tmap(const CUtensorMap* tm) { asm volatile("prefetch.tensormap [%0];" ::"l"(tm) : "memory"); }
__device__ __forceinline__ uint32_t mapa(uint32_t addr, uint32_t rank) {
  uint32_t r;
  asm("mapa.shared::cluster.u32 %0, %1, %2;" : "=r"(r) : "r"(addr), "r"(rank));
  return r;
}
__device__ __forceinline__ void mbar_arrive_cluster(uint32_t bar) {
  asm volatile("mbarrier.arrive.shared::cluster.b64 _, [%0];" ::"r"(bar) : "memory");
}
__device__ __forceinline__ void cluster_arrive() { asm volatile("barrier.cluster.arrive.relaxed.aligned;" ::: "memory"); }
__device__ __forceinline__ void cluster_wait() { asm volatile("barrier.cluster.wait.aligned;" ::: "memory"); }
__device__ __forceinline__ void stsm_x4_t(uint32_t addr, uint32_t a, uint32_t b, uint32_t c, uint32_t d) {
  asm volatile("stmatrix.sync.aligned.m8n8.x4.trans.shared.b16 [%0], {%1,%2,%3,%4};" ::"r"(addr), "r"(a), "r"(b), "r"(c), "r"(d) : "memory");
}
__device__ __forceinline__ void stsm_x4(uint32_t addr, uint32_t a, uint32_t b, uint32_t c, uint32_t d) {
  asm volatile("stmatrix.sync.aligned.m8n8.x4.shared.b16 [%0], {%1,%2,%3,%4};" ::"r"(addr), "r"(a), "r"(b), "r"(c), "r"(d) : "memory");
}
__device__ __forceinline__ void tma_store2d(const CUtensorMap* tm, uint32_t src, int c0, int c1) {
  asm volatile("cp.async.bulk.tensor.2d.global.shared::cta.bulk_group [%0, {%2, %3}], [%1];"
               ::"l"(tm), "r"(src), "r"(c0), "r"(c1) : "memory");
}
__device__ __forceinline__ void bulk_store(void* dst, uint32_t src, uint32_t bytes) {
  asm volatile("cp.async.bulk.global.shared::cta.bulk_group [%0], [%1], %2;" ::"l"(dst), "r"(src), "r"(bytes) : "memory");
}
__device__ __forceinline__ void bulk_load(uint32_t dst, const void* src, uint32_t bytes, uint32_t bar) {
  asm volatile("cp.async.bulk.shared::cluster.global.mbarrier::complete_tx::bytes [%0], [%1], %2, [%3];" ::"r"(dst), "l"(src), "r"(bytes), "r"(bar) : "memory");
}
__device__ __forceinline__ void bulk_commit() { asm volatile("cp.async.bulk.commit_group;" ::: "memory"); }
__device__ __forceinline__ void bulk_wait_read0() { asm volatile("cp.async.bulk.wait_group.read 0;" ::: "memory"); }
template <int N> __device__ __forceinline__ void bulk_wait() { asm volatile("cp.async.bulk.wait_group %0;" ::"n"(N) : "memory"); }
__device__ __forceinline__ void fence_async_smem() { asm volatile("fence.proxy.async.shared::cta;" ::: "memory"); }
__device__ __forceinline__ void named_bar(int id, int n) { asm volatile("bar.sync %0, %1;" ::"r"(id), "r"(n) : "memory"); }
__device__ __forceinline__ void wg_fence() { asm volatile("wgmma.fence.sync.aligned;" ::: "memory"); }
__device__ __forceinline__ void wg_commit() { asm volatile("wgmma.commit_group.sync.aligned;" ::: "memory"); }
template <int N> __device__ __forceinline__ void wg_wait() { asm volatile("wgmma.wait_group.sync.aligned %0;" ::"n"(N) : "memory"); }
__device__ __forceinline__ uint64_t make_desc(uint32_t addr, uint32_t lbo, uint32_t sbo, uint32_t swz) {
  return (uint64_t)((addr & 0x3FFFF) >> 4) | ((uint64_t)(lbo >> 4) << 16) | ((uint64_t)(sbo >> 4) << 32) | ((uint64_t)swz << 62);
}
__device__ __forceinline__ void red_relaxed_add(unsigned* p, unsigned v) {
  asm volatile("red.relaxed.gpu.global.add.u32 [%0], %1;" ::"l"(p), "r"(v) : "memory");
}
__device__ __forceinline__ unsigned ld_relaxed(const unsigned* p) {
  unsigned v;
  asm volatile("ld.relaxed.gpu.global.u32 %0, [%1];" : "=r"(v) : "l"(p) : "memory");
  return v;
}
__device__ __forceinline__ uint32_t pack_bf16(float lo, float hi) {
  uint32_t r;
  asm("cvt.rn.bf16x2.f32 %0, %1, %2;" : "=r"(r) : "f"(hi), "f"(lo));
  return r;
}
__device__ __forceinline__ uint32_t as_u32(bf162 v) { return *reinterpret_cast<uint32_t*>(&v); }
__device__ __forceinline__ bf162 as_bf162(uint32_t v) { return *reinterpret_cast<bf162*>(&v); }

#define R4(d, b) "+f"(d[b + 0]), "+f"(d[b + 1]), "+f"(d[b + 2]), "+f"(d[b + 3])
#define R8(d, b) R4(d, b), R4(d, b + 4)
__device__ __forceinline__ void wgmma_n128(float* d, uint64_t da, uint64_t db) {
  asm volatile(
      "wgmma.mma_async.sync.aligned.m64n128k16.f32.bf16.bf16 "
      "{%0,%1,%2,%3,%4,%5,%6,%7,%8,%9,%10,%11,%12,%13,%14,%15,%16,%17,%18,%19,%20,%21,%22,%23,%24,%25,%26,%27,%28,%29,%30,%31,"
      "%32,%33,%34,%35,%36,%37,%38,%39,%40,%41,%42,%43,%44,%45,%46,%47,%48,%49,%50,%51,%52,%53,%54,%55,%56,%57,%58,%59,%60,%61,%62,%63}, "
      "%64, %65, 1, 1, 1, 0, 1;"
      : R8(d, 0), R8(d, 8), R8(d, 16), R8(d, 24), R8(d, 32), R8(d, 40), R8(d, 48), R8(d, 56)
      : "l"(da), "l"(db));
}
__device__ __forceinline__ void wgmma_n64(float* d, uint64_t da, uint64_t db) {
  asm volatile(
      "wgmma.mma_async.sync.aligned.m64n64k16.f32.bf16.bf16 "
      "{%0,%1,%2,%3,%4,%5,%6,%7,%8,%9,%10,%11,%12,%13,%14,%15,%16,%17,%18,%19,%20,%21,%22,%23,%24,%25,%26,%27,%28,%29,%30,%31}, "
      "%32, %33, 1, 1, 1, 0, 1;"
      : R8(d, 0), R8(d, 8), R8(d, 16), R8(d, 24)
      : "l"(da), "l"(db));
}
__device__ __forceinline__ void wgmma_n80(float* d, uint64_t da, uint64_t db) {
  asm volatile(
      "wgmma.mma_async.sync.aligned.m64n80k16.f32.bf16.bf16 "
      "{%0,%1,%2,%3,%4,%5,%6,%7,%8,%9,%10,%11,%12,%13,%14,%15,%16,%17,%18,%19,%20,%21,%22,%23,%24,%25,%26,%27,%28,%29,%30,%31,"
      "%32,%33,%34,%35,%36,%37,%38,%39}, %40, %41, 1, 1, 1, 1, 0;"
      : R8(d, 0), R8(d, 8), R8(d, 16), R8(d, 24), R8(d, 32)
      : "l"(da), "l"(db));
}
__device__ __forceinline__ void wgmma_n48_tt(float* d, uint64_t da, uint64_t db) {
  asm volatile(
      "wgmma.mma_async.sync.aligned.m64n48k16.f32.bf16.bf16 "
      "{%0,%1,%2,%3,%4,%5,%6,%7,%8,%9,%10,%11,%12,%13,%14,%15,%16,%17,%18,%19,%20,%21,%22,%23}, %24, %25, 1, 1, 1, 1, 1;"
      : R8(d, 0), R8(d, 8), R8(d, 16)
      : "l"(da), "l"(db));
}
template <int SD, int TB> __device__ __forceinline__ void wgr32(float* d, uint32_t a0, uint32_t a1, uint32_t a2, uint32_t a3, uint64_t db) {
  asm volatile(
      "wgmma.mma_async.sync.aligned.m64n32k16.f32.bf16.bf16 "
      "{%0,%1,%2,%3,%4,%5,%6,%7,%8,%9,%10,%11,%12,%13,%14,%15}, {%16,%17,%18,%19}, %20, %21, 1, 1, %22;"
      : R8(d, 0), R8(d, 8) : "r"(a0), "r"(a1), "r"(a2), "r"(a3), "l"(db), "n"(SD), "n"(TB));
}
template <int SD, int TB> __device__ __forceinline__ void wgr40(float* d, uint32_t a0, uint32_t a1, uint32_t a2, uint32_t a3, uint64_t db) {
  asm volatile(
      "wgmma.mma_async.sync.aligned.m64n40k16.f32.bf16.bf16 "
      "{%0,%1,%2,%3,%4,%5,%6,%7,%8,%9,%10,%11,%12,%13,%14,%15,%16,%17,%18,%19}, {%20,%21,%22,%23}, %24, %25, 1, 1, %26;"
      : R8(d, 0), R8(d, 8), R4(d, 16) : "r"(a0), "r"(a1), "r"(a2), "r"(a3), "l"(db), "n"(SD), "n"(TB));
}
template <int SD, int TB> __device__ __forceinline__ void wgr48(float* d, uint32_t a0, uint32_t a1, uint32_t a2, uint32_t a3, uint64_t db) {
  asm volatile(
      "wgmma.mma_async.sync.aligned.m64n48k16.f32.bf16.bf16 "
      "{%0,%1,%2,%3,%4,%5,%6,%7,%8,%9,%10,%11,%12,%13,%14,%15,%16,%17,%18,%19,%20,%21,%22,%23}, {%24,%25,%26,%27}, %28, %29, 1, 1, %30;"
      : R8(d, 0), R8(d, 8), R8(d, 16) : "r"(a0), "r"(a1), "r"(a2), "r"(a3), "l"(db), "n"(SD), "n"(TB));
}
template <int SD, int TB> __device__ __forceinline__ void wgr56(float* d, uint32_t a0, uint32_t a1, uint32_t a2, uint32_t a3, uint64_t db) {
  asm volatile(
      "wgmma.mma_async.sync.aligned.m64n56k16.f32.bf16.bf16 "
      "{%0,%1,%2,%3,%4,%5,%6,%7,%8,%9,%10,%11,%12,%13,%14,%15,%16,%17,%18,%19,%20,%21,%22,%23,%24,%25,%26,%27}, {%28,%29,%30,%31}, %32, %33, 1, 1, %34;"
      : R8(d, 0), R8(d, 8), R8(d, 16), R4(d, 24) : "r"(a0), "r"(a1), "r"(a2), "r"(a3), "l"(db), "n"(SD), "n"(TB));
}
__device__ __forceinline__ uint32_t lds32(uint32_t a) { uint32_t v; asm volatile("ld.shared.u32 %0, [%1];" : "=r"(v) : "r"(a)); return v; }
__device__ __forceinline__ float lds32f(uint32_t a) { float v; asm volatile("ld.shared.f32 %0, [%1];" : "=f"(v) : "r"(a)); return v; }
__device__ __forceinline__ uint32_t lds16(uint32_t a) { uint16_t v; asm volatile("ld.shared.u16 %0, [%1];" : "=h"(v) : "r"(a)); return v; }
__device__ __forceinline__ float4 lds128f(uint32_t a) { float4 v; asm volatile("ld.shared.v4.f32 {%0,%1,%2,%3}, [%4];" : "=f"(v.x), "=f"(v.y), "=f"(v.z), "=f"(v.w) : "r"(a)); return v; }
__device__ __forceinline__ uint2 lds64u(uint32_t a) { uint2 v; asm volatile("ld.shared.v2.u32 {%0,%1}, [%2];" : "=r"(v.x), "=r"(v.y) : "r"(a)); return v; }
__device__ __forceinline__ uint4 lds128u(uint32_t a) { uint4 v; asm volatile("ld.shared.v4.u32 {%0,%1,%2,%3}, [%4];" : "=r"(v.x), "=r"(v.y), "=r"(v.z), "=r"(v.w) : "r"(a)); return v; }
__device__ __forceinline__ void sts16(uint32_t a, uint32_t v) { asm volatile("st.shared.u16 [%0], %1;" ::"r"(a), "h"((uint16_t)v) : "memory"); }
__device__ __forceinline__ void sts32(uint32_t a, uint32_t v) { asm volatile("st.shared.u32 [%0], %1;" ::"r"(a), "r"(v) : "memory"); }
__device__ __forceinline__ void sts64f(uint32_t a, float x, float y) { asm volatile("st.shared.v2.f32 [%0], {%1,%2};" ::"r"(a), "f"(x), "f"(y) : "memory"); }
__device__ __forceinline__ void sts128f(uint32_t a, float x, float y, float z, float w) { asm volatile("st.shared.v4.f32 [%0], {%1,%2,%3,%4};" ::"r"(a), "f"(x), "f"(y), "f"(z), "f"(w) : "memory"); }
__device__ __forceinline__ void sts128u(uint32_t a, uint32_t x, uint32_t y, uint32_t z, uint32_t w) { asm volatile("st.shared.v4.u32 [%0], {%1,%2,%3,%4};" ::"r"(a), "r"(x), "r"(y), "r"(z), "r"(w) : "memory"); }
__device__ __forceinline__ void ldsm4(uint32_t addr, uint32_t* r) {
  asm volatile("ldmatrix.sync.aligned.m8n8.x4.shared.b16 {%0,%1,%2,%3}, [%4];" : "=r"(r[0]), "=r"(r[1]), "=r"(r[2]), "=r"(r[3]) : "r"(addr));
}
__device__ __forceinline__ void ldsm4t(uint32_t addr, uint32_t* r) {
  asm volatile("ldmatrix.sync.aligned.m8n8.x4.trans.shared.b16 {%0,%1,%2,%3}, [%4];" : "=r"(r[0]), "=r"(r[1]), "=r"(r[2]), "=r"(r[3]) : "r"(addr));
}
__device__ __forceinline__ float bf_lo(uint32_t v) { return __uint_as_float(v << 16); }
__device__ __forceinline__ float bf_hi(uint32_t v) { return __uint_as_float(v & 0xffff0000u); }
__device__ __forceinline__ uint32_t ldg16(const bf16* p) {
  uint32_t v;
  asm volatile("ld.global.nc.u16 %0, [%1];" : "=r"(v) : "l"(p));
  return v;
}
__device__ __forceinline__ float2 cmul(float2 a, float2 b) { return make_float2(fmaf(a.x, b.x, -a.y * b.y), fmaf(a.x, b.y, a.y * b.x)); }
__device__ __forceinline__ float2 csqr(float2 a) { return make_float2(fmaf(a.x, a.x, -a.y * a.y), (a.x + a.x) * a.y); }
__device__ __forceinline__ float2 cexp_p2(float ar2, float fh, float fl, float l) {
  float m;
  asm("ex2.approx.f32 %0, %1;" : "=f"(m) : "f"(ar2 * l));
  float ph = fh * l;
  ph = fmaf(fl, l, ph - rintf(ph)) * 6.283185307f;
  return make_float2(m * __cosf(ph), m * __sinf(ph));
}
__device__ __forceinline__ void st_cplx8(uint32_t a, const float2* v) {
  sts128u(a, pack_bf16(v[0].x, v[1].x), pack_bf16(v[2].x, v[3].x), pack_bf16(v[4].x, v[5].x), pack_bf16(v[6].x, v[7].x));
  sts128u(a + 128, pack_bf16(v[0].y, v[1].y), pack_bf16(v[2].y, v[3].y), pack_bf16(v[4].y, v[5].y), pack_bf16(v[6].y, v[7].y));
}

constexpr int G1_STAGES = 3, G1_TX = 40960;
constexpr int SM_X = 0;
constexpr int SM_W = 49152;
constexpr int G2_STAGES = 4, G2_STAGE_BYTES = 26624;
constexpr int SM_AT = 7 * G2_STAGE_BYTES;
constexpr int SM_OUT = SM_AT + 20480;
constexpr int SM_KT = 122880, KT_BYTES = 4096, KT_COPY = 1984;
constexpr int TB_K0 = 336, TB_E1 = 464, TB_O1 = 560, TB_E2 = 656, TB_O2 = 752, TB_E3 = 848, TB_O3 = 944;
constexpr int SM_U0 = SM_KT + 5 * KT_BYTES;
constexpr int U0_PL = 592, U0_BYTES = 8 * U0_PL + 16;
constexpr int SM_XS = (SM_U0 + 5 * U0_BYTES + 127) & ~127;
constexpr int X1_PL = 1184, X1_G = 144, X1_BYTES = 4 * X1_PL, X3_B = 544;
constexpr int XO_1E = 0, XO_1O = X1_BYTES, XO_2E = 2 * X1_BYTES, XO_2O = XO_2E + 3072, XO_3E = XO_2O + 3072, XO_3O = XO_3E + 4 * X3_B;
constexpr int XS_BYTES = XO_3O + 4 * X3_B;
constexpr int PO_1 = XO_1E - 256 * 4, PO_2 = XO_2E - 512 * 4, PO_3 = XO_3E - 1024 * 4;
constexpr int SM_USTG = SM_XS;
constexpr int KG_BYTES = 14336, KG_B = 8192;
constexpr int SM_KG = SM_USTG + 32768;
constexpr int SM_MISC = 229376;
static_assert(SM_XS + 3 * XS_BYTES <= SM_MISC && SM_KG + 2 * KG_BYTES <= SM_MISC && SM_KG + KG_BYTES >= SM_XS + 2 * XS_BYTES, "smem");
static_assert(SM_OUT + 20480 <= SM_MISC && 4 * G2_STAGE_BYTES <= SM_KT, "smem");
constexpr int SM_B1 = SM_MISC + 512;
constexpr int SM_GATE = SM_B1 + 384;
constexpr int SM_GOUT = SM_GATE + 160;
constexpr int SM_TR = SM_MISC + 1280;
constexpr int SM_TOTAL = SM_MISC + 2048;
constexpr int SMEM_BYTES = SM_TOTAL + 1024;

struct Params {
  const bf16 *u, *Are, *Aim, *Bre, *Bim, *Cre, *Cim, *logdt, *Dsk, *w1, *b1, *w2, *b2, *gate_w;
  bf16* gate;
  unsigned *hflag, *aflag, *epoch;
};

__device__ __forceinline__ uint32_t u0_chunk(uint32_t u0, int q) { return u0 + (q & 7) * U0_PL + (q >> 3) * 16; }

__device__ __forceinline__ void build_x(uint32_t xs, uint32_t u0, int w4, int lane) {
  if (w4 < 2) {
    const int q = lane - 4 + 28 * w4;
    uint32_t w[20];
#pragma unroll
    for (int i = 0; i < 5; i++) {
      const uint4 v = lds128u(u0_chunk(u0, 4 * q - 1 + i));
      w[4 * i] = v.x; w[4 * i + 1] = v.y; w[4 * i + 2] = v.z; w[4 * i + 3] = v.w;
    }
    float t[32];
#pragma unroll
    for (int k = 0; k < 16; k++) {
      const float p2 = bf_lo(w[k + 2]) + bf_hi(w[k + 2]);
      t[2 * k] = bf_hi(w[k + 1]) + p2;
      t[2 * k + 1] = p2 + bf_lo(w[k + 3]);
    }
    const uint32_t o = xs + (lane & 3) * X1_PL + (lane >> 2) * X1_G + w4 * 64;
#pragma unroll
    for (int r = 0; r < 4; r++) {
      sts128u(o + XO_1E + r * 16, pack_bf16(t[r], t[4 + r]), pack_bf16(t[8 + r], t[12 + r]), pack_bf16(t[16 + r], t[20 + r]), pack_bf16(t[24 + r], t[28 + r]));
      const uint32_t sel = (r & 1) ? 0x7632u : 0x5410u;
      const int b = 3 + (r >> 1);
      sts128u(o + XO_1O + r * 16, __byte_perm(w[b], w[b + 2], sel), __byte_perm(w[b + 4], w[b + 6], sel), __byte_perm(w[b + 8], w[b + 10], sel),
              __byte_perm(w[b + 12], w[b + 14], sel));
    }
  }
#pragma unroll 1
  for (int rnd = w4 < 2 ? 1 : 0; rnd < 2; rnd++) {
    const int m = (rnd ? 64 + 32 * w4 : 32 * (w4 - 2)) + lane - 1;
    const uint2 c0 = lds64u(u0_chunk(u0, m - 1) + 8);
    const uint4 c1 = lds128u(u0_chunk(u0, m)), c2 = lds128u(u0_chunk(u0, m + 1));
    const uint32_t w[10] = {c0.x, c0.y, c1.x, c1.y, c1.z, c1.w, c2.x, c2.y, c2.z, c2.w};
    float s[18];
    s[0] = 0.f;
#pragma unroll
    for (int k = 0; k < 17; k++) s[k + 1] = s[k] + ((k & 1) ? bf_hi(w[k >> 1]) : bf_lo(w[k >> 1]));
#define WIN(hi, lo) pack_bf16(s[hi] - s[lo], s[hi + 1] - s[lo + 1]), pack_bf16(s[hi + 2] - s[lo + 2], s[hi + 3] - s[lo + 3]), \
                    pack_bf16(s[hi + 4] - s[lo + 4], s[hi + 5] - s[lo + 5]), pack_bf16(s[hi + 6] - s[lo + 6], s[hi + 7] - s[lo + 7])
    sts128u(xs + XO_2E + (m + 1) * 16, WIN(7, 2));
    sts128u(xs + XO_2O + (m + 1) * 16, WIN(10, 7));
    if (m <= 126) {
      const int i = m + 1, j = m + 2;
      sts128u(xs + XO_3O + (i & 1) * (2 * X3_B) + (i >> 6) * X3_B + ((i >> 1) & 31) * 16, WIN(8, 1));
      if (m <= 125) sts128u(xs + XO_3E + (j & 1) * (2 * X3_B) + (j >> 6) * X3_B + ((j >> 1) & 31) * 16, WIN(9, 0));
      else sts128u(xs + XO_3E, 0, 0, 0, 0);
    }
#undef WIN
  }
}

#define TQ(k)
template <int I0, int I1> __device__ __forceinline__ void load_tab(uint32_t a, uint32_t* R) {
#pragma unroll
  for (int i = I0; i < I1; i++) R[i] = lds32(a + 16 * i);
}
__device__ __forceinline__ void conv_hi(uint32_t xs, uint32_t u0, uint32_t kt, int barid, int w4, int lane, uint32_t tq) {
  const int g = lane >> 2, c = lane & 3, o = 8 * w4 + g;
  const uint32_t ta = kt + (g & 1) * KT_COPY + ((g & 1) - o + 2 * c - 64) * 2;
  float a3[16], a2[24], b2[16], a1[28];
  {
    uint32_t E[12], O[12];
    load_tab<0, 12>(ta + TB_E2 * 2, E);
    load_tab<0, 12>(ta + TB_O2 * 2, O);
    const uint64_t d2 = make_desc(xs + XO_2E, 128, 512, 0);
    TQ(0);
    wg_fence();
    wgr48<0, 1>(a2, E[8], E[4], E[9], E[5], d2);
    wgr32<0, 1>(b2, E[0], 0u, E[1], 0u, d2);
    wgr48<1, 1>(a2, E[10], E[6], E[11], E[7], d2 + 16);
    wgr32<1, 1>(b2, E[2], 0u, E[3], 0u, d2 + 16);
    wgr48<1, 1>(a2, O[8], O[4], O[9], O[5], d2 + 192);
    wgr32<1, 1>(b2, O[0], 0u, O[1], 0u, d2 + 192);
    wgr48<1, 1>(a2, O[10], O[6], O[11], O[7], d2 + 192 + 16);
    wgr32<1, 1>(b2, O[2], 0u, O[3], 0u, d2 + 192 + 16);
    wg_commit();
  }
  TQ(1);
  float cr[8];
  {
    const float k1024 = bf_lo(lds16(kt + (TB_E2 - 63) * 2));
#pragma unroll
    for (int hf = 0; hf < 2; hf++) {
      const int x = 16 * o + 8 * hf + 2 * c;
      const uint32_t pa = u0_chunk(u0, (x - 4) >> 3) + ((x - 4) & 7) * 2, pb = u0_chunk(u0, (x - 2) >> 3) + ((x - 2) & 7) * 2;
#pragma unroll
      for (int b = 0; b < 2; b++) {
        const uint32_t va = lds32(pa + b * 128), vb = lds32(pb + b * 128);
        cr[4 * hf + 2 * b] = k1024 * (bf_lo(va) + bf_hi(va));
        cr[4 * hf + 2 * b + 1] = k1024 * (bf_hi(va) + bf_lo(vb));
      }
    }
  }
  TQ(2);
  wg_wait<0>();
  TQ(3);
  float f2[12];
#pragma unroll
  for (int i = 0; i < 12; i++) {
    const int b = i >> 1, e = i & 1;
    f2[i] = a2[4 * b + e];
    if (b >= 1) f2[i] += a2[4 * b - 2 + e];
    if (b >= 2) f2[i] += b2[4 * b - 8 + e];
  }
  const uint64_t d1 = make_desc(xs + XO_1E, X1_PL, X1_G, 0);
  constexpr int P2 = 2 * X1_PL >> 4, G = X1_G >> 4, OO = X1_BYTES >> 4;
  {
    uint32_t E[12], O[12];
    load_tab<4, 12>(ta + TB_E3 * 2, E);
    load_tab<4, 12>(ta + TB_O3 * 2, O);
    const uint64_t d3 = make_desc(xs + XO_3E, 128, X3_B, 0);
#pragma unroll
    for (int i = 0; i < 16; i++) a3[i] = (i & 2) ? 0.f : cr[(i >> 2) * 2 + (i & 1)];
    asm volatile("" : R8(a3, 0), R8(a3, 8));
    wg_fence();
    wgr32<1, 1>(a3, E[8], E[4], E[9], E[5], d3);
    wgr32<1, 1>(a3, E[10], E[6], E[11], E[7], d3 + 16);
    wgr32<1, 1>(a3, O[8], O[4], O[9], O[5], d3 + (4 * X3_B >> 4));
    wgr32<1, 1>(a3, O[10], O[6], O[11], O[7], d3 + (4 * X3_B >> 4) + 16);
    wg_commit();
  }
  TQ(4);
  named_bar(barid, 128);
  TQ(5);
#pragma unroll
  for (int b = 0; b < 6; b++) {
    const int t = 256 * b + 8 * o + 2 * c;
    sts64f(xs + XO_2E + (t ^ (((2 * b + (w4 >> 1)) & 3) << 3)) * 4, f2[2 * b], f2[2 * b + 1]);
  }
  {
    uint32_t E1[12], O1[12];
    load_tab<0, 12>(ta + TB_E1 * 2, E1);
    TQ(6);
    wg_wait<0>();
    TQ(7);
    load_tab<0, 12>(ta + TB_O1 * 2, O1);
#pragma unroll
    for (int i = 0; i < 8; i++) cr[i] = a3[(i >> 1) * 4 + (i & 1)] + ((i & 2) ? a3[(i >> 2) * 8 + 2 + (i & 1)] : 0.f);
    asm volatile("" : R8(cr, 0));
    wg_fence();
    wgr56<0, 0>(a1, E1[4], E1[0], E1[5], E1[1], d1);
    wgr56<1, 0>(a1, E1[6], E1[2], E1[7], E1[3], d1 + P2);
    wgr56<1, 0>(a1, E1[8], 0u, E1[9], 0u, d1 + G);
    wgr56<1, 0>(a1, E1[10], 0u, E1[11], 0u, d1 + G + P2);
    wgr56<1, 0>(a1, O1[4], O1[0], O1[5], O1[1], d1 + OO);
    wgr56<1, 0>(a1, O1[6], O1[2], O1[7], O1[3], d1 + OO + P2);
    wgr56<1, 0>(a1, O1[8], 0u, O1[9], 0u, d1 + OO + G);
    wgr56<1, 0>(a1, O1[10], 0u, O1[11], 0u, d1 + OO + G + P2);
    wg_commit();
  }
  TQ(8);
  wg_wait<0>();
  TQ(9);
  named_bar(barid, 128);
  TQ(10);
#pragma unroll
  for (int hf = 0; hf < 2; hf++)
#pragma unroll
    for (int b = 0; b < 2; b++) {
      const int t = 512 * b + 16 * o + 8 * hf + 2 * c;
      sts64f(xs + XO_3E + (t ^ (w4 << 3)) * 4, cr[4 * hf + 2 * b], cr[4 * hf + 2 * b + 1]);
    }
  {
    const float sx = __shfl_xor_sync(0xffffffffu, a1[26], 2), sy = __shfl_xor_sync(0xffffffffu, a1[27], 2);
    const int be = c >> 1;
#pragma unroll
    for (int b = 0; b < 7; b++) {
      const int t = 128 * (7 * be + b) + 4 * o + 2 * (c & 1);
      float x = a1[4 * b], y = a1[4 * b + 1];
      if (b) { x += a1[4 * b - 2]; y += a1[4 * b - 1]; }
      else if (be) { x += sx; y += sy; }
      sts64f(xs + XO_1E + (t ^ (((2 + b - be) & 3) << 3)) * 4, x, y);
    }
  }
}
__device__ __forceinline__ void conv_lo(uint32_t xs, uint32_t u0, uint32_t kt, int barid, uint32_t bar_p, uint32_t dsk2, int w4, int lane, uint32_t tq) {
  const int g = lane >> 2, c = lane & 3;
  float acc[16];
  const uint32_t ta = kt + (g & 1) * KT_COPY + (TB_K0 + (g & 1) - g + 2 * c - 16 * w4 - 280) * 2;
  const uint64_t d0 = make_desc(u0 - 80, U0_PL, 128, 0);
  {
    uint32_t R[21];
#pragma unroll
    for (int i = 0; i < 21; i++) R[i] = lds32(ta + 16 * i);
    TQ(0);
    wg_fence();
#pragma unroll
    for (int s = 0; s < 10; s++) {
      const uint64_t d = d0 + ((2 * s + 6) & 7) * (U0_PL >> 4) + ((2 * s + 6) >> 3);
      if (s == 0) wgr32<0, 0>(acc, R[1], R[0], R[2], R[1], d);
      else wgr32<1, 0>(acc, R[2 * s + 1], R[2 * s], R[2 * s + 2], R[2 * s + 1], d);
    }
    wg_commit();
  }
  TQ(1);
  if (bar_p) mbar_wait(bar_p, 0);
  named_bar(barid, 128);
  TQ(2);
  float ps[16];
  const uint32_t pa = xs + (((16 * w4 + g) ^ (c << 3)) + 128 * c) * 4;
#pragma unroll
  for (int j = 0; j < 4; j++)
#pragma unroll
    for (int q = 0; q < 4; q++) {
      const uint32_t a = (pa ^ ((q >> 1) * 32)) + (512 * j + 64 * (q & 1)) * 4;
      float v = 0.f;
      if (j > 0 || c >= 2) v = lds32f(a + (uint32_t)PO_1);
      if (j > 0) v += lds32f(a + PO_2);
      if (j > 1) v += lds32f(a + PO_3);
      ps[4 * j + q] = v;
    }
  TQ(3);
  wg_wait<0>();
  TQ(4);
  {
    uint32_t R[23];
#pragma unroll
    for (int i = 0; i < 23; i++) R[i] = lds32(ta + 16 * (20 + i));
#pragma unroll
    for (int i = 0; i < 16; i++) acc[i] += ps[i];
    asm volatile("" : R8(acc, 0), R8(acc, 8));
    wg_fence();
#pragma unroll
    for (int j = 0; j < 11; j++) {
      const int s = 10 + j;
      wgr32<1, 0>(acc, R[2 * j + 1], R[2 * j], R[2 * j + 2], R[2 * j + 1], d0 + ((2 * s + 6) & 7) * (U0_PL >> 4) + ((2 * s + 6) >> 3));
    }
    wg_commit();
  }
  TQ(5);
  uint32_t uu[8];
  const int mi = lane >> 3, n0 = 8 * (mi >> 1) + (lane & 7), ck = 2 * w4 + (mi & 1);
  ldsm4t(u0 + ck * U0_PL + n0 * 16, uu);
  ldsm4t(u0 + ck * U0_PL + n0 * 16 + 256, uu + 4);
  named_bar(barid, 128);
  TQ(6);
  wg_wait<0>();
  TQ(7);
#pragma unroll
  for (int i = 0; i < 8; i++)
    uu[i] = as_u32(__hadd2_rn(as_bf162(pack_bf16(acc[2 * i], acc[2 * i + 1])), __hmul2_rn(as_bf162(uu[i]), as_bf162(dsk2))));
  const uint32_t oa = kt + n0 * 128 + ((ck ^ (lane & 7)) << 4);
  stsm_x4_t(oa, uu[0], uu[1], uu[2], uu[3]);
  stsm_x4_t(oa + 2048, uu[4], uu[5], uu[6], uu[7]);
}

__device__ __forceinline__ void kt_put(uint32_t kt, int idx, uint32_t v) {
  sts16(kt + idx * 2, v);
  sts16(kt + KT_COPY + 2 + idx * 2, v);
}
__device__ __forceinline__ void kt_store(uint32_t kt, int r, int col, float val, int d) {
  const uint32_t v = pack_bf16(val, 0.f) & 0xffffu;
  int idx, idx2 = -1;
  if (col < 8) idx = TB_K0 - 8 * r - col;
  else if (col < 12) {
    idx = ((col & 1) ? TB_O1 : TB_E1) - 2 * r - ((col - 9) >> 1);
    if (col == 8 && r == 0) { idx = TB_K0 - 256; idx2 = TB_K0 - 257; }
  } else if (col < 16) {
    idx = ((col & 1) ? TB_O2 : TB_E2 + 1) - 32 * ((col - 12) >> 1) - r;
    if (col == 12 && r == 0) { idx = TB_E1 - 63; idx2 = TB_O1 - 64; }
  } else {
    idx = ((r & 1) ? TB_O3 : TB_E3 + 1) - 16 * (col - 16) - (r >> 1);
    if (col == 16 && r == 0) idx = TB_E2 - 63;
    if (col > 20 || (col == 20 && r != 0)) idx = -1;
  }
  if (idx >= 0) kt_put(kt, idx, v);
  if (idx2 >= 0) kt_put(kt, idx2, v);
}

__global__ void __cluster_dims__(2, 1, 1) __launch_bounds__(640, 1)
fused_kernel(const __grid_constant__ CUtensorMap tm_x, const __grid_constant__ CUtensorMap tm_w1,
             const __grid_constant__ CUtensorMap tm_hst, const __grid_constant__ CUtensorMap tm_hld,
             const __grid_constant__ CUtensorMap tm_w2, const __grid_constant__ CUtensorMap tm_aT,
             const __grid_constant__ CUtensorMap tm_ast, const __grid_constant__ CUtensorMap tm_out,
             const __grid_constant__ CUtensorMap tm_ug, const Params p) {
  extern __shared__ uint8_t smem_raw[];
  const uint32_t sraw = smem_u32(smem_raw);
  const uint32_t sb = (sraw + 1023) & ~1023u;
  uint8_t* sm = smem_raw + (sb - sraw);
  const int tid = threadIdx.x, warp = __shfl_sync(0xffffffffu, tid >> 5, 0), lane = tid & 31;
  const int cta = blockIdx.x, cl = cta >> 1, rk = cta & 1;
  const bool has1 = cl < 64;
  const int idx = cl < 64 ? (cl & 7) * 8 + (cl >> 3) : 64;
  const int sl = (idx & 3) + ((idx >> 3) & 1) * 4, tt = 2 * (((idx >> 2) & 1) + (idx >> 4) * 2) + rk;
  const int dt5 = idx % 5, T2 = 2 * (idx / 5) + rk;
  const uint32_t bar_full1 = sb + SM_MISC;
  const uint32_t bar_empty1 = bar_full1 + 24;
  const uint32_t bar_full2 = bar_empty1 + 24;
  const uint32_t bar_empty2 = bar_full2 + 32;
  const uint32_t bar_ringfree = bar_empty2 + 32;
  const uint32_t bar_at = bar_ringfree + 8;
  const uint32_t bar_gate = bar_at + 8;
  const uint32_t bar_hst = bar_gate + 8;
  const uint32_t bar_go = bar_hst + 24;
  const uint32_t bar_cvc = bar_go + 8;
  const uint32_t bar_u = bar_cvc + 8;
  const uint32_t bar_p4 = bar_u + 8;
  const uint32_t bar_par = bar_p4 + 8;
  const uint32_t peer_off = mapa(sb, rk ^ 1) - sb;
  const int uo = (5 * cta) & 7;
  if (tid == 0) TS(0);

  if (tid == 512) {
    for (int i = 0; i < G1_STAGES; i++) { mbar_init(bar_full1 + 8 * i, 1); mbar_init(bar_empty1 + 8 * i, 16); }
    if (has1) {
      asm volatile("fence.mbarrier_init.release.cluster;" ::: "memory");
#pragma unroll
      for (int kb = 0; kb < G1_STAGES; kb++) {
        mbar_expect_tx(bar_full1 + 8 * kb, G1_TX);
        tma_load2d(sb + SM_X + kb * 16384, &tm_x, kb * 64, tt * 128, bar_full1 + 8 * kb);
      }
    }
  }
  if (tid == 544) prefetch_tmap(&tm_w1);
  if (warp == 19 && has1) {
    if (lane == 0) {
      mbar_init(bar_par, 1);
      mbar_init(bar_u, 1);
      asm volatile("fence.mbarrier_init.release.cluster;" ::: "memory");
      mbar_expect_tx(bar_par, 11520);
      mbar_expect_tx(bar_u, uo > 3 ? 32768 : 16384);
    }
    __syncwarp();
    if (lane < 30) {
      const int a = lane / 5, ch = lane - 5 * a;
      const bf16* pp = a == 0 ? p.Are : a == 1 ? p.Aim : a == 2 ? p.Bre : a == 3 ? p.Bim : a == 4 ? p.Cre : p.Cim;
      bulk_load(sb + SM_KT + ch * KT_BYTES + a * 384, pp + (5 * cta + ch) * NM_, 384, bar_par);
    }
    if (lane < (uo > 3 ? 8 : 4)) tma_load2d(sb + SM_USTG + lane * 4096, &tm_ug, 5 * cta - uo + (lane >> 2) * 8, (lane & 3) * 256, bar_u);
  }
  if (tid == 96) {
    for (int i = 0; i < G2_STAGES; i++) { mbar_init(bar_full2 + 8 * i, 1); mbar_init(bar_empty2 + 8 * i, 16); }
    mbar_init(bar_ringfree, 4);
    mbar_init(bar_at, 1);
    mbar_init(bar_gate, 8);
    for (int i = 0; i < 3; i++) mbar_init(bar_hst + 8 * i, 8);
    mbar_init(bar_go, 8);
    mbar_init(bar_cvc, 4);
    mbar_init(bar_p4, 4);
    asm volatile("fence.mbarrier_init.release.cluster;" ::: "memory");
  }
  if (tid >= 128 && tid < 128 + 96 && has1) ((uint32_t*)(sm + SM_B1))[tid - 128] = ((const uint32_t*)(p.b1 + sl * 192))[tid - 128];
  cluster_arrive();
  cluster_wait();

  const int wg = warp >> 2, w4 = warp & 3, g = lane >> 2, c = lane & 3;
  if (warp >= 16) {
    asm volatile("setmaxnreg.dec.sync.aligned.u32 24;");
    const int r0 = T2 * 80;
    if (warp == 16) {
      if (lane == 0) {
        if (has1) {
#pragma unroll
          for (int kb = G1_STAGES; kb < 10; kb++) {
            const int s = kb % G1_STAGES;
            mbar_wait(bar_empty1 + 8 * s, (kb / G1_STAGES - 1) & 1);
            tma_load2d(sb + SM_X + s * 16384, &tm_x, kb * 64, tt * 128, bar_full1 + 8 * s);
            mbar_expect_tx(bar_full1 + 8 * s, G1_TX);
          }
          mbar_wait(bar_ringfree, 0);
        }
        const int c0 = dt5 * 128 + rk * 64;
#pragma unroll 1
        for (int i4 = 0; i4 < 6; i4++) {
#pragma unroll
          for (int s = 0; s < 4; s++) {
            const int bx = i4 < 2 ? 12 * i4 + 3 * s + 2 : 6 * (i4 - 2) + 3 * (s >> 1) + (s & 1);
            if (i4) mbar_wait(bar_empty2 + 8 * s, (i4 - 1) & 1);
            tma_load2d_mc(sb + rk * 8192 + s * G2_STAGE_BYTES, &tm_w2, c0, bx * 64, bar_full2 + 8 * s);
            mbar_expect_tx(bar_full2 + 8 * s, G2_STAGE_BYTES);
          }
        }
      }
    } else if (warp == 17) {
      const unsigned ep1 = p.epoch[cta] + 1;
      if (has1) {
        if (lane == 0) {
#pragma unroll
          for (int kb = 0; kb < 10; kb++) {
            const int s = kb % G1_STAGES;
            if (kb >= G1_STAGES) mbar_wait(bar_empty1 + 8 * s, (kb / G1_STAGES - 1) & 1);
            tma_load3d_mc(sb + SM_W + s * 24576 + rk * 12288, &tm_w1, 0, kb * 64 + rk * 32, sl * 3, bar_full1 + 8 * s);
          }
        }
        __syncwarp();
        mbar_wait(bar_ringfree, 0);
      }
      const int t0 = r0 >> 7, t1 = min(15, (r0 + 79) >> 7);
      const unsigned* fl = p.hflag + ((((lane & 8) ? t1 : t0) * 8 + (lane & 7)) * 2 + (lane >> 4)) * 8;
      unsigned rdy = 0;
#pragma unroll 1
      for (int i4 = 0; i4 < 6; i4++) {
#pragma unroll
        for (int s = 0; s < 4; s++) {
          const int bx = i4 < 2 ? 12 * i4 + 3 * s + 2 : 6 * (i4 - 2) + 3 * (s >> 1) + (s & 1);
          const unsigned need = i4 < 2 ? 0x101u << (4 * i4 + s) : 0x1010000u << (2 * (i4 - 2) + (s >> 1));
#pragma unroll 1
          for (int it = 0; (rdy & need) != need; ++it) {
            rdy = __ballot_sync(0xffffffffu, (int)(ld_relaxed(fl) - ep1) >= 0);
            if (it > SPIN_LIMIT) SPIN_FAIL;
          }
          if (lane == 0) {
            if (i4) mbar_wait(bar_empty2 + 8 * s, (i4 - 1) & 1);
            if (i4 == 0 && s == 0) TS(6);
            tma_load2d(sb + s * G2_STAGE_BYTES + 16384, &tm_hld, 0, bx * L_ + r0, bar_full2 + 8 * s);
          }
          __syncwarp();
        }
        if (i4 == 1 && lane == 0) bulk_load(sb + SM_GATE, p.gate + r0, 160, bar_at);
      }
    } else if (warp == 18) {
      const unsigned ep1 = p.epoch[cta] + 1;
      if (lane == 0 && has1 && sl < 7) tma_pf2d(&tm_x, (3 + sl) * 64, tt * 128);
      if (lane == 1 && has1 && tt < 14) tma_pf3d(&tm_w1, 0, 192 + tt * 32, sl * 3);
      if (lane == 2) { prefetch_tmap(&tm_hst); prefetch_tmap(&tm_hld); prefetch_tmap(&tm_w2); }
      if (lane == 3) { prefetch_tmap(&tm_aT); prefetch_tmap(&tm_ast); prefetch_tmap(&tm_out); }
      __syncwarp();
      if (lane == 0) {
        if (has1) {
          mbar_wait(bar_empty1, 0);
          l2_prefetch(p.w2 + (size_t)cta * 7680, 15360);
#pragma unroll
          for (int b = 0; b < 2; b++) {
            mbar_wait(bar_hst + 8 + 8 * b, 0);
            tma_store2d(&tm_hst, sb + SM_X + b * 16384, 0, (sl * 3 + b) * L_ + tt * 128);
          }
          bulk_commit();
          TS(4);
          bulk_wait_read0();
          mbar_arrive(bar_ringfree);
          mbar_arrive_cluster(bar_ringfree + peer_off);
          bulk_wait<0>();
          red_relaxed_add(p.hflag + (tt * 8 + sl) * 16 + 8, 1);
          mbar_wait(bar_cvc, 0);
        }
        const unsigned ta = ep1 * 128;
#pragma unroll 1
        for (int it = 0; (int)(ld_relaxed(p.aflag + dt5 * 32) - ta) < 0; ++it) {
          __nanosleep(50);
          if (it > SPIN_LIMIT) SPIN_FAIL;
        }
        TS(22);
        tma_load2d(sb + SM_AT, &tm_aT, r0, dt5 * 128, bar_at);
        mbar_expect_tx(bar_at, 20480 + 160);
        mbar_wait(bar_at, 0);
        p.epoch[cta] = ep1;
      }
    } else if (lane == 0 && has1) {
      mbar_wait(bar_gate, 0);
      bulk_store(p.gate + tt * 128 + sl * 16, sb + SM_GOUT, 32);
      mbar_wait(bar_hst, 0);
      tma_store2d(&tm_hst, sb + SM_X + 2 * 16384, 0, (sl * 3 + 2) * L_ + tt * 128);
      bulk_commit();
      bulk_wait_read0();
      mbar_arrive(bar_ringfree);
      mbar_arrive_cluster(bar_ringfree + peer_off);
      bulk_wait<0>();
      red_relaxed_add(p.hflag + (tt * 8 + sl) * 16, 1);
      TS(5);
    }
  } else {
    if (has1) {
      if (warp < 8) {
        asm volatile("setmaxnreg.inc.sync.aligned.u32 128;");
        float acc[96];
#pragma unroll
        for (int i = 0; i < 96; i++) acc[i] = 0.f;
        {
          const uint64_t da0 = make_desc(sb + SM_X + wg * 8192, 16, 1024, 1);
          const uint64_t db0 = make_desc(sb + SM_W, 4096, 1024, 1);
          const uint32_t rel = bar_empty1 + (lane ? peer_off : 0u);
          uint32_t so = 0, ph = 0, prev = 0;
#pragma unroll 1
          for (int kb = 0; kb < 10; kb++) {
            mbar_wait(bar_full1 + so * 8, ph);
            if (tid == 0 && kb == 0) TS(1);
            if (tid == 0) TR(kb);
            const uint64_t da = da0 + so * (16384 >> 4), db = db0 + so * (24576 >> 4);
            wg_fence();
#pragma unroll
            for (int k = 0; k < 4; k++) {
              wgmma_n128(acc, da + k * 2, db + (k >> 1) * 768 + (k & 1) * 128);
              wgmma_n64(acc + 64, da + k * 2, db + (k >> 1) * 768 + (k & 1) * 128 + 512);
            }
            wg_commit();
            const uint32_t cur = so;
            if (++so == G1_STAGES) { so = 0; ph ^= 1; }
            if (kb > 0 && kb + 2 < 10) {
              wg_wait<1>();
              if (lane < 2) mbar_arrive_cluster(rel + prev * 8);
            }
            prev = cur;
          }
        }
        wg_wait<0>();
        if (tid == 0) TS(3);
        const uint32_t* b1s = (const uint32_t*)(sm + SM_B1);
        const int mrow = w4 * 16 + (lane & 7) + ((lane >> 3) & 1) * 8;
        const bf162 zero2 = __float2bfloat162_rn(0.f);
#pragma unroll
        for (int j0 = 0; j0 < 24; j0 += 2) {
          const int j = (j0 + 16) % 24;
          uint32_t r[4];
#pragma unroll
          for (int q = 0; q < 4; q++) {
            const int jj = j + (q >> 1);
            bf162 v = as_bf162(pack_bf16(acc[4 * jj + 2 * (q & 1)], acc[4 * jj + 2 * (q & 1) + 1]));
            v = __hadd2_rn(v, as_bf162(b1s[jj * 4 + c]));
            v = __hmax2(v, zero2);
            v = __hmul2_rn(v, v);
            r[q] = as_u32(v);
          }
          const int chunk = (j & 7) + (lane >> 4);
          stsm_x4(sb + SM_X + (j >> 3) * 16384 + wg * 8192 + mrow * 128 + ((chunk ^ (mrow & 7)) << 4), r[0], r[1], r[2], r[3]);
          if ((j & 7) == 6) {
            fence_async_smem();
            __syncwarp();
            if (lane == 0) mbar_arrive(bar_hst + (j0 >> 3) * 8);
            if (j0 == 6) asm volatile("setmaxnreg.dec.sync.aligned.u32 112;");
          }
        }
      } else {
        const int wgs = wg & 1;
        const int gam = w4 & 1, role = w4 >> 1;
        const uint32_t ldt0 = ldg16(p.logdt + 5 * cta + 2 * wgs + gam), ldt4 = ldg16(p.logdt + 5 * cta + 4);
        {
          const int t = tt * 128 + sl * 16 + (warp - 8) * 2;
          const uint32_t* xr = (const uint32_t*)(p.u + (size_t)t * D_);
          const uint32_t* gw = (const uint32_t*)p.gate_w;
          uint32_t xv[20], gv[10];
#pragma unroll
          for (int i = 0; i < 20; i++) xv[i] = __ldg(xr + lane + 32 * i);
#pragma unroll
          for (int i = 0; i < 10; i++) gv[i] = __ldg(gw + lane + 32 * i);
          if (tid >= 384 && tid < 384 + 100) {
            const int i = 2 * (tid - 384);
            sts128u(sb + SM_U0 + (i / 40) * U0_BYTES + ((i % 40) / 5) * U0_PL + (i % 5) * 16, 0, 0, 0, 0);
            sts128u(sb + SM_U0 + (i / 40) * U0_BYTES + (((i + 1) % 40) / 5) * U0_PL + ((i + 1) % 5) * 16, 0, 0, 0, 0);
          }
          float s0 = 0.f, s1 = 0.f;
#pragma unroll
          for (int i = 0; i < 10; i++) {
            const bf162 v0 = __hmul2_rn(as_bf162(xv[i]), as_bf162(gv[i])), v1 = __hmul2_rn(as_bf162(xv[i + 10]), as_bf162(gv[i]));
            s0 += __low2float(v0) + __high2float(v0);
            s1 += __low2float(v1) + __high2float(v1);
          }
#pragma unroll
          for (int o = 16; o; o >>= 1) { s0 += __shfl_xor_sync(0xffffffffu, s0, o); s1 += __shfl_xor_sync(0xffffffffu, s1, o); }
          if (lane < 2) {
            const float z = __bfloat162float(__float2bfloat16_rn(lane ? s1 : s0));
            ((bf16*)(sm + SM_GOUT))[(warp - 8) * 2 + lane] = __float2bfloat16_rn(1.f / (1.f + __expf(-z)));
            fence_async_smem();
          }
          __syncwarp();
          if (lane == 0) mbar_arrive(bar_gate);
        }
        mbar_wait(bar_par, 0);
        uint32_t po = sb + SM_KT + (2 * wgs + gam) * KT_BYTES + lane * 2, pr[6];
        pr[0] = lds16(po); pr[1] = lds16(po + 384);
        if (role) { pr[2] = lds16(po + 768); pr[3] = lds16(po + 1152); pr[4] = lds16(po + 1536); pr[5] = lds16(po + 1920); }
        if (tid == 256) TS(14);
        const uint32_t kgA = sb + SM_KG + (wgs ^ 1) * KG_BYTES;
        const uint32_t kst = kgA + (role ? KG_B + gam * 3072 : gam * 4096) + (lane >> 3) * 256 + (lane & 7) * 16;
        const uint64_t dka = make_desc(kgA, 128, 1024, 0), dkb = make_desc(kgA + KG_B, 128, 1024, 0);
        auto u_round = [&](int rnd) {
          mbar_wait(bar_u, rnd);
#pragma unroll 1
          for (int bx = 0; bx < (uo > 3 ? 2 : 1); bx++) {
            const int chl = g + 8 * bx - uo;
            const uint32_t o = sb + SM_U0 + chl * U0_BYTES + 80 + (rnd * 16 + w4 * 4) * 16 + c * 4;
#pragma unroll
            for (int i = 0; i < 8; i++) {
              uint32_t r[4];
              ldsm4t(sb + SM_USTG + bx * 16384 + ((w4 * 8 + i) * 32 + lane) * 16, r);
              if (chl >= 0 && chl < 5) {
#pragma unroll
                for (int q = 0; q < 4; q++) sts32(o + ((i & 1) * 4 + q) * U0_PL + (i >> 1) * 16, r[q]);
              }
            }
          }
          named_bar(4, 128);
        };
#pragma unroll 1
        for (int job = wgs; job < 3; job += 2) {
          const int nch = job == 2 ? 3 : 6;
          const float dt = __bfloat162float(__float2bfloat16_rn(expf(bf_lo(job == 2 ? ldt4 : ldt0))));
          float acc[24];
#pragma unroll
          for (int i = 0; i < 24; i++) acc[i] = 0.f;
#pragma unroll 1
          for (int k = 0; k < nch; k++) {
            const uint32_t tq = (job == 0 && (k == 2 || k == 3) && (tid & 191) == 0) ? sb + SM_TR + 40 + (k - 2) * 24 + role * 48 : 0u;
            TQ(0);
            const float ar2 = dt * bf_lo(pr[0]) * 1.4426950409f, ai = role ? dt * bf_lo(pr[1]) : -dt * bf_lo(pr[1]);
            const float fh = ai * 0.15915494f, fl = fmaf(ai, 6.4206382e-9f, fmaf(ai, 0.15915494f, -fh));
            const float2 cc = cmul(make_float2(bf_lo(pr[4]), bf_lo(pr[5])), make_float2(dt * bf_lo(pr[2]), dt * bf_lo(pr[3])));
            po += 64;
            if (k + 1 == nch) po = sb + SM_KT + 4 * KT_BYTES + 192 * gam + lane * 2;
            pr[0] = lds16(po); pr[1] = lds16(po + 384);
            float2 v[8];
            if (role == 0) {
              v[0] = make_float2(1.f, 0.f);
              v[1] = cexp_p2(ar2, fh, fl, 8.f);
              const float2 f1 = cexp_p2(ar2, fh, fl, 64.f);
              v[2] = csqr(v[1]); v[3] = cmul(v[2], v[1]); v[4] = csqr(v[2]); v[5] = cmul(v[4], v[1]); v[6] = csqr(v[3]); v[7] = cmul(v[4], v[3]);
              const float2 f2 = csqr(f1), f3 = cmul(f2, f1);
              TQ(1);
              wg_wait<0>();
              TQ(2);
              named_bar(3 + wgs, 128);
              TQ(3);
              st_cplx8(kst, v);
#pragma unroll
              for (int j = 1; j < 4; j++) {
                const float2 f = j == 1 ? f1 : j == 2 ? f2 : f3;
                float2 x[8];
                x[0] = f;
#pragma unroll
                for (int i = 1; i < 8; i++) x[i] = cmul(v[i], f);
                st_cplx8(kst + j * 1024, x);
              }
            } else {
              pr[2] = lds16(po + 768); pr[3] = lds16(po + 1152); pr[4] = lds16(po + 1536); pr[5] = lds16(po + 1920);
              const float2 e1 = cexp_p2(ar2, fh, fl, 1.f), h1 = cexp_p2(ar2, fh, fl, 256.f), h4 = cexp_p2(ar2, fh, fl, 1024.f);
              const float2 e2 = csqr(e1), e4 = csqr(e2), e6 = cmul(e4, e2), h2 = csqr(h1), h3 = cmul(h2, h1);
              v[0] = cc; v[2] = cmul(cc, e2); v[4] = cmul(cc, e4); v[6] = cmul(cc, e6);
              v[1] = cmul(cc, e1); v[3] = cmul(v[2], e1); v[5] = cmul(v[4], e1); v[7] = cmul(v[6], e1);
              TQ(1);
              wg_wait<0>();
              TQ(2);
              named_bar(3 + wgs, 128);
              TQ(3);
              st_cplx8(kst, v);
              float2 x[8];
              x[0] = cmul(v[0], h1); x[1] = cmul(v[2], h1); x[2] = cmul(v[4], h1); x[3] = cmul(v[6], h1);
              x[4] = cmul(v[0], h2); x[5] = cmul(v[4], h2); x[6] = cmul(v[0], h3); x[7] = cmul(v[4], h3);
              st_cplx8(kst + 1024, x);
              x[1] = cmul(x[0], h4); x[2] = cmul(x[4], h4); x[3] = cmul(x[6], h4); x[0] = cmul(cc, h4); x[4] = cmul(x[0], h4);
              x[5] = x[6] = x[7] = make_float2(0.f, 0.f);
              st_cplx8(kst + 2048, x);
            }
            TQ(4);
            fence_async_smem();
            named_bar(3 + wgs, 128);
            TQ(5);
            wg_fence();
#pragma unroll
            for (int ks = 0; ks < 4; ks++) wgmma_n48_tt(acc, dka + ks * 16, dkb + ks * 16);
            wg_commit();
            if (wgs && k == 1) {
              wg_wait<0>();
              u_round(0);
              if (tid == 384) mbar_expect_tx(bar_u, uo > 3 ? 32768 : 16384);
              if (tid < 384 + (uo > 3 ? 8 : 4)) tma_load2d(sb + SM_USTG + lane * 4096, &tm_ug, 5 * cta - uo + (lane >> 2) * 8, 1024 + (lane & 3) * 256, bar_u);
              __syncwarp();
            }
          }
          {
            const uint32_t za = sb + SM_KT + 2 * job * KT_BYTES + (tid & 127) * 16;
            sts128u(za, 0, 0, 0, 0); sts128u(za + 2048, 0, 0, 0, 0);
            if (job < 2) { sts128u(za + 4096, 0, 0, 0, 0); sts128u(za + 6144, 0, 0, 0, 0); }
          }
          wg_wait<0>();
          named_bar(3 + wgs, 128);
          float kv[12];
#pragma unroll
          for (int i = 0; i < 12; i++) kv[i] = (w4 >> 1) ? acc[12 + i] : acc[i];
          bool wr = true;
          if (job == 2) {
            const uint32_t xa = kgA + ((w4 & 1) * 32 + lane) * 48;
            if (w4 >> 1) {
              sts128f(xa, kv[0], kv[1], kv[2], kv[3]); sts128f(xa + 16, kv[4], kv[5], kv[6], kv[7]); sts128f(xa + 32, kv[8], kv[9], kv[10], kv[11]);
            }
            named_bar(3 + wgs, 128);
            wr = (w4 >> 1) == 0;
            if (wr) {
#pragma unroll
              for (int i = 0; i < 3; i++) {
                const float4 o = lds128f(xa + 16 * i);
                kv[4 * i] += o.x; kv[4 * i + 1] += o.y; kv[4 * i + 2] += o.z; kv[4 * i + 3] += o.w;
              }
            }
          }
          if (wr) {
            const int chl = job == 2 ? 4 : 2 * job + (w4 >> 1);
#pragma unroll
            for (int i = 0; i < 12; i++)
              kt_store(sb + SM_KT + chl * KT_BYTES, 16 * (w4 & 1) + g + 8 * ((i >> 1) & 1), 8 * (i >> 2) + 2 * c + (i & 1), kv[i], 5 * cta + chl);
          }
          if (tid == 256) TS(15 + (job >> 1));
        }
        if (wgs) {
          u_round(1);
          asm volatile("bar.arrive 5, 256;" ::: "memory");
        } else {
          named_bar(5, 256);
        }
        if (tid == 384) TS(17);
#pragma unroll 1
        for (int ch = wgs ? 0 : 4; ch != 2 && ch != 5; ch++)
          build_x(sb + SM_XS + (ch == 4 ? 2 : ch) * XS_BYTES, sb + SM_U0 + ch * U0_BYTES + 80, w4, lane);
        fence_async_smem();
        __syncwarp();
        if (lane == 0) mbar_arrive(bar_go);
        if (tid == 384) TS(18);
        asm volatile("setmaxnreg.inc.sync.aligned.u32 112;");
      }
      uint32_t tasks = wg == 0 ? 0x2u : wg == 1 ? 0x3u : 0x32132u;
      uint32_t chans = wg < 2 ? 0x4u : wg == 2 ? 0x22200u : 0x33311u;
      mbar_wait(bar_go, 0);
      if (tid == 256) TS(20);
      uint32_t stored = 0;
#pragma unroll 1
      for (; tasks; tasks >>= 4, chans >>= 4) {
        const int ty = tasks & 15, ch = chans & 15;
        int ln = lane;
        asm volatile("" : "+r"(ln));
        const uint32_t xs = sb + SM_XS + (ch == 4 ? 2 : ch & 1) * XS_BYTES, u0 = sb + SM_U0 + ch * U0_BYTES + 80, kt = sb + SM_KT + ch * KT_BYTES;
        if ((tid & 127) == 0) TR(32 + wg * 16 + (__clz(tasks) >> 2));
        if (ty == 1) {
          build_x(xs, u0, w4, ln);
          fence_async_smem();
          named_bar(1 + wg, 128);
        } else if (ty == 2) {
          conv_hi(xs, u0, kt, 1 + wg, w4, ln, tid == 256 ? sb + SM_TR + 512 + (ch >> 1) * 128 : 0u);
          if (ch == 4) {
            __syncwarp();
            if (lane == 0) mbar_arrive(bar_p4);
          }
        } else {
          const uint32_t dk = ldg16(p.Dsk + 5 * cta + ch);
          conv_lo(xs, u0, kt, 1 + wg, ch == 4 ? bar_p4 : 0u, dk | (dk << 16), w4, ln, tid == 256 ? sb + SM_TR + 512 + 64 + (ch >> 1) * 128 : 0u);
          fence_async_smem();
          named_bar(1 + wg, 128);
          if ((tid & 127) == 0) {
            tma_store2d(&tm_ast, kt, 0, (5 * cta + ch) * 32);
            bulk_commit();
            stored |= 1u << ch;
          }
        }
      }
      if ((tid & 127) == 0) TR(32 + wg * 16 + 8);
      if (wg == 0) named_bar(1, 128);
      if ((tid & 127) == 0) {
        if (stored) bulk_wait_read0();
        mbar_arrive(bar_cvc);
        if (wg >= 2) {
          bulk_wait<0>();
          if (tid == 256) TS(21);
          for (int ch = 0; ch < 5; ch++)
            if (stored >> ch & 1) red_relaxed_add(p.aflag + ((5 * cta + ch) >> 7) * 32, 1);
        }
      }
      __syncwarp();
    }
    else if (warp < 8) asm volatile("setmaxnreg.inc.sync.aligned.u32 112;");
    if (warp < 8) {
      float acc[40];
#pragma unroll
      for (int i = 0; i < 40; i++) acc[i] = 0.f;
      const int d0 = dt5 * 128 + wg * 64 + w4 * 16 + g;
      const bf162 b2a = __bfloat162bfloat162(p.b2[d0]), b2b = __bfloat162bfloat162(p.b2[d0 + 8]);
      {
        const uint64_t da0 = make_desc(sb + wg * 8192, 16, 1024, 1);
        const uint64_t db0 = make_desc(sb + 16384, 16, 1024, 1);
        const uint32_t rel = bar_empty2 + (lane ? peer_off : 0u);
#pragma unroll 1
        for (int kb = 0; kb < 24; kb++) {
          const uint32_t so = kb & 3;
          mbar_wait(bar_full2 + so * 8, (kb >> 2) & 1);
          if (tid == 0 && kb == 0) TS(7);
          if (tid == 0 && kb == 12) TS(8);
          if (tid == 0) TR(96 + kb);
          const uint64_t da = da0 + so * (G2_STAGE_BYTES >> 4), db = db0 + so * (G2_STAGE_BYTES >> 4);
          wg_fence();
#pragma unroll
          for (int k = 0; k < 4; k++) wgmma_n80(acc, da + k * 128, db + k * 2);
          wg_commit();
          if (kb > 0 && kb <= 20) {
            wg_wait<1>();
            if (lane < 2) mbar_arrive_cluster(rel + ((kb - 1) & 3) * 8);
          }
          if (kb == 2 && tid == 128 && has1) {
            bulk_wait<0>();
            red_relaxed_add(p.aflag + ((5 * cta + 4) >> 7) * 32, 1);
          }
        }
      }
      wg_wait<0>();
      if (tid == 0) TS(9);
      mbar_wait(bar_at, 0);
      const uint32_t* gs = (const uint32_t*)(sm + SM_GATE);
      const bf162 one2 = __float2bfloat162_rn(1.f);
#pragma unroll
      for (int j = 0; j < 10; j += 2) {
        uint32_t a[4], r[4];
        ldsm4(sb + SM_AT + (wg * 64 + w4 * 16 + (lane & 15)) * 160 + (j + (lane >> 4)) * 16, a);
#pragma unroll
        for (int q = 0; q < 4; q++) {
          const int jj = j + (q >> 1);
          const bf162 gg = as_bf162(gs[jj * 4 + c]);
          bf162 v = as_bf162(pack_bf16(acc[4 * jj + 2 * (q & 1)], acc[4 * jj + 2 * (q & 1) + 1]));
          v = __hadd2_rn(v, (q & 1) ? b2b : b2a);
          v = __hmul2_rn(v, __hsub2_rn(one2, gg));
          r[q] = as_u32(__hadd2_rn(__hmul2_rn(as_bf162(a[q]), gg), v));
        }
        const int tr = 8 * (j + (lane >> 4)) + (lane & 7);
        const int chunk = 2 * w4 + ((lane >> 3) & 1);
        stsm_x4_t(sb + SM_OUT + wg * 10240 + tr * 128 + ((chunk ^ (tr & 7)) << 4), r[0], r[1], r[2], r[3]);
      }
      fence_async_smem();
      named_bar(1 + wg, 128);
      if ((tid & 127) == 0) {
        tma_store2d(&tm_out, sb + SM_OUT + wg * 10240, dt5 * 128 + wg * 64, T2 * 80);
        bulk_commit();
        bulk_wait_read0();
        if (tid == 0) TS(10);
      }
    }
  }
}

typedef CUresult (*EncodeFn)(CUtensorMap*, CUtensorMapDataType, cuuint32_t, void*, const cuuint64_t*, const cuuint64_t*,
                             const cuuint32_t*, const cuuint32_t*, CUtensorMapInterleave, CUtensorMapSwizzle,
                             CUtensorMapL2promotion, CUtensorMapFloatOOBfill);

static void make_map(EncodeFn fn, CUtensorMap* m, const void* ptr, uint64_t inner, uint64_t outer, uint32_t box_in, uint32_t box_out,
                     CUtensorMapSwizzle swz) {
  cuuint64_t dims[2] = {inner, outer};
  cuuint64_t strides[1] = {inner * 2};
  cuuint32_t box[2] = {box_in, box_out};
  cuuint32_t es[2] = {1, 1};
  CUresult r = fn(m, CU_TENSOR_MAP_DATA_TYPE_BFLOAT16, 2, const_cast<void*>(ptr), dims, strides, box, es, CU_TENSOR_MAP_INTERLEAVE_NONE, swz,
     CU_TENSOR_MAP_L2_PROMOTION_L2_256B, CU_TENSOR_MAP_FLOAT_OOB_FILL_NONE);
  (void)r;
}

extern "C" void kernel_launch(void* const* d_in, const int* in_sizes, int n_in, void* d_out, int out_size) {
  static EncodeFn fn = nullptr;
  static CUtensorMap tm_x, tm_w1, tm_hst, tm_hld, tm_w2, tm_aT, tm_ast, tm_out, tm_ug;
  static void *pg = nullptr, *phf = nullptr, *paf = nullptr, *pep = nullptr;
  static const void *c_x = nullptr, *c_w1 = nullptr, *c_w2 = nullptr, *c_out = nullptr;
  if (!fn) {
    void* f = nullptr;
    cudaDriverEntryPointQueryResult qr;
    cudaGetDriverEntryPoint("cuTensorMapEncodeTiled", &f, cudaEnableDefault, &qr);
    fn = (EncodeFn)f;
    cudaFuncSetAttribute(fused_kernel, cudaFuncAttributeMaxDynamicSharedMemorySize, SMEM_BYTES);
    void *ph, *pa;
    cudaGetSymbolAddress(&ph, g_h);
    cudaGetSymbolAddress(&pa, g_aT);
    cudaGetSymbolAddress(&pg, g_gate);
    cudaGetSymbolAddress(&phf, g_hflag);
    cudaGetSymbolAddress(&paf, g_aflag);
    cudaGetSymbolAddress(&pep, g_epoch);
    make_map(fn, &tm_hst, ph, 64, 24 * L_, 64, 128, CU_TENSOR_MAP_SWIZZLE_128B);
    make_map(fn, &tm_hld, ph, 64, 24 * L_, 64, 80, CU_TENSOR_MAP_SWIZZLE_128B);
    make_map(fn, &tm_aT, pa, L_, D_, 80, 128, CU_TENSOR_MAP_SWIZZLE_NONE);
    make_map(fn, &tm_ast, pa, 64, 32 * D_, 64, 32, CU_TENSOR_MAP_SWIZZLE_128B);
  }
  if (c_x != d_in[0]) {
    make_map(fn, &tm_x, d_in[0], D_, L_, 64, 128, CU_TENSOR_MAP_SWIZZLE_128B);
    make_map(fn, &tm_ug, d_in[0], D_, L_, 8, 256, CU_TENSOR_MAP_SWIZZLE_NONE);
    c_x = d_in[0];
  }
  if (c_w1 != d_in[10]) {
    cuuint64_t dims[3] = {64, (cuuint64_t)D_, 24};
    cuuint64_t strides[2] = {(cuuint64_t)F_ * 2, 128};
    cuuint32_t box[3] = {64, 32, 3};
    cuuint32_t es[3] = {1, 1, 1};
    fn(&tm_w1, CU_TENSOR_MAP_DATA_TYPE_BFLOAT16, 3, d_in[10], dims, strides, box, es, CU_TENSOR_MAP_INTERLEAVE_NONE,
       CU_TENSOR_MAP_SWIZZLE_128B, CU_TENSOR_MAP_L2_PROMOTION_L2_256B, CU_TENSOR_MAP_FLOAT_OOB_FILL_NONE);
    c_w1 = d_in[10];
  }
  if (c_w2 != d_in[12]) { make_map(fn, &tm_w2, d_in[12], D_, F_, 64, 64, CU_TENSOR_MAP_SWIZZLE_128B); c_w2 = d_in[12]; }
  if (c_out != d_out) { make_map(fn, &tm_out, d_out, D_, L_, 64, 80, CU_TENSOR_MAP_SWIZZLE_128B); c_out = d_out; }
  Params p;
  p.u = (const bf16*)d_in[0];
  p.Are = (const bf16*)d_in[1];
  p.Aim = (const bf16*)d_in[2];
  p.Bre = (const bf16*)d_in[3];
  p.Bim = (const bf16*)d_in[4];
  p.Cre = (const bf16*)d_in[5];
  p.Cim = (const bf16*)d_in[6];
  p.logdt = (const bf16*)d_in[7];
  p.Dsk = (const bf16*)d_in[8];
  p.w1 = (const bf16*)d_in[10];
  p.b1 = (const bf16*)d_in[11];
  p.w2 = (const bf16*)d_in[12];
  p.b2 = (const bf16*)d_in[13];
  p.gate_w = (const bf16*)d_in[14];
  p.gate = (bf16*)pg;
  p.hflag = (unsigned*)phf;
  p.aflag = (unsigned*)paf;
  p.epoch = (unsigned*)pep;
  fused_kernel<<<NCTA, 640, SMEM_BYTES, cudaStreamPerThread>>>(tm_x, tm_w1, tm_hst, tm_hld, tm_w2, tm_aT, tm_ast, tm_out, tm_ug, p);
}
```

```cpp
#include <cuda_runtime.h>
#include <cuda_bf16.h>
#include <cuda_fp16.h>
#include <cuda.h>
#include <stdint.h>
#include <string.h>

typedef __nv_bfloat16 bf16;
typedef __nv_bfloat162 bf162;

constexpr int L_ = 2048, D_ = 640, NM_ = 192, F_ = 1536;
constexpr int NCTA = 128;

__device__ bf16 g_h[L_ * F_];
__device__ bf16 g_aT[D_ * L_];
__device__ bf16 g_uT[D_ * 2368];
__device__ bf16 g_w2p[F_ * D_];
__device__ unsigned g_gate[L_];
__device__ unsigned g_flag[(256 + 16) * 8];
__device__ unsigned g_epoch[NCTA];
__device__ unsigned g_err;
#define TS(i)
#define TR(i)

#define SPIN_LIMIT 2000000
#define SPIN_FAIL __trap()
__device__ __forceinline__ uint32_t smem_u32(const void* p) { return (uint32_t)__cvta_generic_to_shared(p); }
__device__ __forceinline__ void mbar_init(uint32_t bar, uint32_t cnt) {
  asm volatile("mbarrier.init.shared::cta.b64 [%0], %1;" ::"r"(bar), "r"(cnt) : "memory");
}
__device__ __forceinline__ void mbar_arrive(uint32_t bar) {
  asm volatile("mbarrier.arrive.shared::cta.b64 _, [%0];" ::"r"(bar) : "memory");
}
__device__ __forceinline__ void mbar_expect_tx(uint32_t bar, uint32_t bytes) {
  asm volatile("mbarrier.arrive.expect_tx.shared::cta.b64 _, [%0], %1;" ::"r"(bar), "r"(bytes) : "memory");
}
__device__ __forceinline__ void mbar_wait(uint32_t bar, uint32_t parity) {
  asm volatile(
      "{\n.reg .pred p;\n.reg .u32 c;\nmov.u32 c, 0;\n"
      "WL:\nmbarrier.try_wait.parity.shared::cta.b64 p, [%0], %1;\n@p bra WD;\n"
      "add.u32 c, c, 1;\nsetp.lt.u32 p, c, 4000000;\n@p bra WL;\ntrap;\nWD:\n}"
      ::"r"(bar), "r"(parity) : "memory");
}
__device__ __forceinline__ void tma_load2d(uint32_t dst, const CUtensorMap* tm, int c0, int c1, uint32_t bar) {
  asm volatile("cp.async.bulk.tensor.2d.shared::cluster.global.mbarrier::complete_tx::bytes [%0], [%1, {%3, %4}], [%2];"
               ::"r"(dst), "l"(tm), "r"(bar), "r"(c0), "r"(c1) : "memory");
}
__device__ __forceinline__ void tma_load3d_mc(uint32_t dst, const CUtensorMap* tm, int c0, int c1, int c2, uint32_t bar) {
  asm volatile("cp.async.bulk.tensor.3d.shared::cluster.global.mbarrier::complete_tx::bytes.multicast::cluster [%0], [%1, {%3, %4, %5}], [%2], %6;"
               ::"r"(dst), "l"(tm), "r"(bar), "r"(c0), "r"(c1), "r"(c2), "h"((uint16_t)3) : "memory");
}
__device__ __forceinline__ void tma_load3d(uint32_t dst, const CUtensorMap* tm, int c0, int c1, int c2, uint32_t bar) {
  asm volatile("cp.async.bulk.tensor.3d.shared::cluster.global.mbarrier::complete_tx::bytes [%0], [%1, {%3, %4, %5}], [%2];"
               ::"r"(dst), "l"(tm), "r"(bar), "r"(c0), "r"(c1), "r"(c2) : "memory");
}
__device__ __forceinline__ void tma_load4d(uint32_t dst, const CUtensorMap* tm, int c0, int c1, int c2, int c3, uint32_t bar) {
  asm volatile("cp.async.bulk.tensor.4d.shared::cluster.global.mbarrier::complete_tx::bytes [%0], [%1, {%3, %4, %5, %6}], [%2];"
               ::"r"(dst), "l"(tm), "r"(bar), "r"(c0), "r"(c1), "r"(c2), "r"(c3) : "memory");
}
__device__ __forceinline__ void tma_store3d(const CUtensorMap* tm, uint32_t src, int c0, int c1, int c2) {
  asm volatile("cp.async.bulk.tensor.3d.global.shared::cta.bulk_group [%0, {%2, %3, %4}], [%1];"
               ::"l"(tm), "r"(src), "r"(c0), "r"(c1), "r"(c2) : "memory");
}
__device__ __forceinline__ void tma_pf3d(const CUtensorMap* tm, int c0, int c1, int c2) {
  asm volatile("cp.async.bulk.prefetch.tensor.3d.L2.global [%0, {%1, %2, %3}];" ::"l"(tm), "r"(c0), "r"(c1), "r"(c2) : "memory");
}
__device__ __forceinline__ void l2_prefetch(const void* p, uint32_t bytes) {
  asm volatile("cp.async.bulk.prefetch.L2.global [%0], %1;" ::"l"(p), "r"(bytes) : "memory");
}
__device__ __forceinline__ void prefetch_tmap(const CUtensorMap* tm) { asm volatile("prefetch.tensormap [%0];" ::"l"(tm) : "memory"); }
__device__ __forceinline__ uint32_t mapa(uint32_t addr, uint32_t rank) {
  uint32_t r;
  asm("mapa.shared::cluster.u32 %0, %1, %2;" : "=r"(r) : "r"(addr), "r"(rank));
  return r;
}
__device__ __forceinline__ void mbar_arrive_cluster(uint32_t bar) {
  asm volatile("mbarrier.arrive.shared::cluster.b64 _, [%0];" ::"r"(bar) : "memory");
}
__device__ __forceinline__ void cluster_arrive() { asm volatile("barrier.cluster.arrive.relaxed.aligned;" ::: "memory"); }
__device__ __forceinline__ void cluster_wait() { asm volatile("barrier.cluster.wait.aligned;" ::: "memory"); }
__device__ __forceinline__ void stsm_x4_t(uint32_t addr, uint32_t a, uint32_t b, uint32_t c, uint32_t d) {
  asm volatile("stmatrix.sync.aligned.m8n8.x4.trans.shared.b16 [%0], {%1,%2,%3,%4};" ::"r"(addr), "r"(a), "r"(b), "r"(c), "r"(d) : "memory");
}
__device__ __forceinline__ void stsm_x4(uint32_t addr, uint32_t a, uint32_t b, uint32_t c, uint32_t d) {
  asm volatile("stmatrix.sync.aligned.m8n8.x4.shared.b16 [%0], {%1,%2,%3,%4};" ::"r"(addr), "r"(a), "r"(b), "r"(c), "r"(d) : "memory");
}
__device__ __forceinline__ void tma_store2d(const CUtensorMap* tm, uint32_t src, int c0, int c1) {
  asm volatile("cp.async.bulk.tensor.2d.global.shared::cta.bulk_group [%0, {%2, %3}], [%1];"
               ::"l"(tm), "r"(src), "r"(c0), "r"(c1) : "memory");
}
__device__ __forceinline__ void bulk_load(uint32_t dst, const void* src, uint32_t bytes, uint32_t bar) {
  asm volatile("cp.async.bulk.shared::cluster.global.mbarrier::complete_tx::bytes [%0], [%1], %2, [%3];" ::"r"(dst), "l"(src), "r"(bytes), "r"(bar) : "memory");
}
__device__ __forceinline__ void bulk_load_mc(uint32_t dst, const void* src, uint32_t bytes, uint32_t bar) {
  asm volatile("cp.async.bulk.shared::cluster.global.mbarrier::complete_tx::bytes.multicast::cluster [%0], [%1], %2, [%3], %4;"
               ::"r"(dst), "l"(src), "r"(bytes), "r"(bar), "h"((uint16_t)3) : "memory");
}
__device__ __forceinline__ void bulk_store(void* dst, uint32_t src, uint32_t bytes) {
  asm volatile("cp.async.bulk.global.shared::cta.bulk_group [%0], [%1], %2;" ::"l"(dst), "r"(src), "r"(bytes) : "memory");
}
__device__ __forceinline__ void bulk_commit() { asm volatile("cp.async.bulk.commit_group;" ::: "memory"); }
__device__ __forceinline__ void bulk_wait_read0() { asm volatile("cp.async.bulk.wait_group.read 0;" ::: "memory"); }
template <int N> __device__ __forceinline__ void bulk_wait() { asm volatile("cp.async.bulk.wait_group %0;" ::"n"(N) : "memory"); }
__device__ __forceinline__ void fence_async_smem() { asm volatile("fence.proxy.async.shared::cta;" ::: "memory"); }
__device__ __forceinline__ void named_bar(int id, int n) { asm volatile("bar.sync %0, %1;" ::"r"(id), "r"(n) : "memory"); }
__device__ __forceinline__ void named_arrive(int id, int n) { asm volatile("bar.arrive %0, %1;" ::"r"(id), "r"(n) : "memory"); }
__device__ __forceinline__ void wg_fence() { asm volatile("wgmma.fence.sync.aligned;" ::: "memory"); }
__device__ __forceinline__ void wg_commit() { asm volatile("wgmma.commit_group.sync.aligned;" ::: "memory"); }
template <int N> __device__ __forceinline__ void wg_wait() { asm volatile("wgmma.wait_group.sync.aligned %0;" ::"n"(N) : "memory"); }
__device__ __forceinline__ uint64_t make_desc(uint32_t addr, uint32_t lbo, uint32_t sbo, uint32_t swz) {
  return (uint64_t)((addr & 0x3FFFF) >> 4) | ((uint64_t)(lbo >> 4) << 16) | ((uint64_t)(sbo >> 4) << 32) | ((uint64_t)swz << 62);
}
__device__ __forceinline__ void red_relaxed_add(unsigned* p, unsigned v) {
  asm volatile("red.relaxed.gpu.global.add.u32 [%0], %1;" ::"l"(p), "r"(v) : "memory");
}
__device__ __forceinline__ unsigned ld_relaxed(const unsigned* p) {
  unsigned v;
  asm volatile("ld.relaxed.gpu.global.u32 %0, [%1];" : "=r"(v) : "l"(p) : "memory");
  return v;
}
__device__ __forceinline__ void st_relaxed(unsigned* p, unsigned v) {
  asm volatile("st.relaxed.gpu.global.u32 [%0], %1;" ::"l"(p), "r"(v) : "memory");
}
__device__ __forceinline__ uint32_t pack_bf16(float lo, float hi) {
  uint32_t r;
  asm("cvt.rn.bf16x2.f32 %0, %1, %2;" : "=r"(r) : "f"(hi), "f"(lo));
  return r;
}
__device__ __forceinline__ uint32_t as_u32(bf162 v) { return *reinterpret_cast<uint32_t*>(&v); }
__device__ __forceinline__ bf162 as_bf162(uint32_t v) { return *reinterpret_cast<bf162*>(&v); }

#define R4(d, b) "+f"(d[b + 0]), "+f"(d[b + 1]), "+f"(d[b + 2]), "+f"(d[b + 3])
#define R8(d, b) R4(d, b), R4(d, b + 4)
__device__ __forceinline__ void wgmma_n192(float* d, uint64_t da, uint64_t db) {
  asm volatile("wgmma.mma_async.sync.aligned.m64n192k16.f32.bf16.bf16 {%0,%1,%2,%3,%4,%5,%6,%7,%8,%9,%10,%11,%12,%13,%14,%15,%16,%17,%18,%19,%20,%21,%22,%23,%24,%25,%26,%27,%28,%29,%30,%31,%32,%33,%34,%35,%36,%37,%38,%39,%40,%41,%42,%43,%44,%45,%46,%47,%48,%49,%50,%51,%52,%53,%54,%55,%56,%57,%58,%59,%60,%61,%62,%63,%64,%65,%66,%67,%68,%69,%70,%71,%72,%73,%74,%75,%76,%77,%78,%79,%80,%81,%82,%83,%84,%85,%86,%87,%88,%89,%90,%91,%92,%93,%94,%95}, %96, %97, 1, 1, 1, 0, 1;"
      : R8(d, 0), R8(d, 8), R8(d, 16), R8(d, 24), R8(d, 32), R8(d, 40), R8(d, 48), R8(d, 56), R8(d, 64), R8(d, 72), R8(d, 80), R8(d, 88)
      : "l"(da), "l"(db));
}
__device__ __forceinline__ void wgmma_n160(float* d, uint64_t da, uint64_t db) {
  asm volatile("wgmma.mma_async.sync.aligned.m64n160k16.f32.bf16.bf16 {%0,%1,%2,%3,%4,%5,%6,%7,%8,%9,%10,%11,%12,%13,%14,%15,%16,%17,%18,%19,%20,%21,%22,%23,%24,%25,%26,%27,%28,%29,%30,%31,%32,%33,%34,%35,%36,%37,%38,%39,%40,%41,%42,%43,%44,%45,%46,%47,%48,%49,%50,%51,%52,%53,%54,%55,%56,%57,%58,%59,%60,%61,%62,%63,%64,%65,%66,%67,%68,%69,%70,%71,%72,%73,%74,%75,%76,%77,%78,%79}, %80, %81, 1, 1, 1, 0, 1;"
      : R8(d, 0), R8(d, 8), R8(d, 16), R8(d, 24), R8(d, 32), R8(d, 40), R8(d, 48), R8(d, 56), R8(d, 64), R8(d, 72)
      : "l"(da), "l"(db));
}
__device__ __forceinline__ void wgmma_n48_tt(float* d, uint64_t da, uint64_t db, uint32_t sd) {
  asm volatile(
      "{.reg .pred p; setp.ne.u32 p, %26, 0;\n"
      "wgmma.mma_async.sync.aligned.m64n48k16.f32.f16.f16 "
      "{%0,%1,%2,%3,%4,%5,%6,%7,%8,%9,%10,%11,%12,%13,%14,%15,%16,%17,%18,%19,%20,%21,%22,%23}, %24, %25, p, 1, 1, 1, 1;}"
      : R8(d, 0), R8(d, 8), R8(d, 16)
      : "l"(da), "l"(db), "r"(sd));
}
template <int SD, int TB> __device__ __forceinline__ void wgr32(float* d, uint32_t a0, uint32_t a1, uint32_t a2, uint32_t a3, uint64_t db) {
  asm volatile(
      "wgmma.mma_async.sync.aligned.m64n32k16.f32.bf16.bf16 "
      "{%0,%1,%2,%3,%4,%5,%6,%7,%8,%9,%10,%11,%12,%13,%14,%15}, {%16,%17,%18,%19}, %20, %21, 1, 1, %22;"
      : R8(d, 0), R8(d, 8) : "r"(a0), "r"(a1), "r"(a2), "r"(a3), "l"(db), "n"(SD), "n"(TB));
}
template <int SD, int TB> __device__ __forceinline__ void wgr48(float* d, uint32_t a0, uint32_t a1, uint32_t a2, uint32_t a3, uint64_t db) {
  asm volatile(
      "wgmma.mma_async.sync.aligned.m64n48k16.f32.bf16.bf16 "
      "{%0,%1,%2,%3,%4,%5,%6,%7,%8,%9,%10,%11,%12,%13,%14,%15,%16,%17,%18,%19,%20,%21,%22,%23}, {%24,%25,%26,%27}, %28, %29, 1, 1, %30;"
      : R8(d, 0), R8(d, 8), R8(d, 16) : "r"(a0), "r"(a1), "r"(a2), "r"(a3), "l"(db), "n"(SD), "n"(TB));
}
__device__ __forceinline__ void wgr64(float* d, uint32_t a0, uint32_t a1, uint32_t a2, uint32_t a3, uint64_t db) {
  asm volatile(
      "wgmma.mma_async.sync.aligned.m64n64k16.f32.bf16.bf16 "
      "{%0,%1,%2,%3,%4,%5,%6,%7,%8,%9,%10,%11,%12,%13,%14,%15,%16,%17,%18,%19,%20,%21,%22,%23,%24,%25,%26,%27,%28,%29,%30,%31}, {%32,%33,%34,%35}, %36, 1, 1, 1, 0;"
      : R8(d, 0), R8(d, 8), R8(d, 16), R8(d, 24) : "r"(a0), "r"(a1), "r"(a2), "r"(a3), "l"(db));
}
__device__ __forceinline__ uint32_t lds32(uint32_t a) { uint32_t v; asm volatile("ld.shared.u32 %0, [%1];" : "=r"(v) : "r"(a)); return v; }
__device__ __forceinline__ float lds32f(uint32_t a) { float v; asm volatile("ld.shared.f32 %0, [%1];" : "=f"(v) : "r"(a)); return v; }
__device__ __forceinline__ uint32_t lds16(uint32_t a) { uint16_t v; asm volatile("ld.shared.u16 %0, [%1];" : "=h"(v) : "r"(a)); return v; }
__device__ __forceinline__ float4 lds128f(uint32_t a) { float4 v; asm volatile("ld.shared.v4.f32 {%0,%1,%2,%3}, [%4];" : "=f"(v.x), "=f"(v.y), "=f"(v.z), "=f"(v.w) : "r"(a)); return v; }
__device__ __forceinline__ uint2 lds64u(uint32_t a) { uint2 v; asm volatile("ld.shared.v2.u32 {%0,%1}, [%2];" : "=r"(v.x), "=r"(v.y) : "r"(a)); return v; }
__device__ __forceinline__ uint4 lds128u(uint32_t a) { uint4 v; asm volatile("ld.shared.v4.u32 {%0,%1,%2,%3}, [%4];" : "=r"(v.x), "=r"(v.y), "=r"(v.z), "=r"(v.w) : "r"(a)); return v; }
__device__ __forceinline__ void sts16(uint32_t a, uint32_t v) { asm volatile("st.shared.u16 [%0], %1;" ::"r"(a), "h"((uint16_t)v) : "memory"); }
__device__ __forceinline__ void sts32(uint32_t a, uint32_t v) { asm volatile("st.shared.u32 [%0], %1;" ::"r"(a), "r"(v) : "memory"); }
__device__ __forceinline__ void sts64f(uint32_t a, float x, float y) { asm volatile("st.shared.v2.f32 [%0], {%1,%2};" ::"r"(a), "f"(x), "f"(y) : "memory"); }
__device__ __forceinline__ void sts128f(uint32_t a, float x, float y, float z, float w) { asm volatile("st.shared.v4.f32 [%0], {%1,%2,%3,%4};" ::"r"(a), "f"(x), "f"(y), "f"(z), "f"(w) : "memory"); }
__device__ __forceinline__ void sts128u(uint32_t a, uint32_t x, uint32_t y, uint32_t z, uint32_t w) { asm volatile("st.shared.v4.u32 [%0], {%1,%2,%3,%4};" ::"r"(a), "r"(x), "r"(y), "r"(z), "r"(w) : "memory"); }
__device__ __forceinline__ void ldsm4(uint32_t addr, uint32_t* r) {
  asm volatile("ldmatrix.sync.aligned.m8n8.x4.shared.b16 {%0,%1,%2,%3}, [%4];" : "=r"(r[0]), "=r"(r[1]), "=r"(r[2]), "=r"(r[3]) : "r"(addr));
}
__device__ __forceinline__ void ldsm4t(uint32_t addr, uint32_t* r) {
  asm volatile("ldmatrix.sync.aligned.m8n8.x4.trans.shared.b16 {%0,%1,%2,%3}, [%4];" : "=r"(r[0]), "=r"(r[1]), "=r"(r[2]), "=r"(r[3]) : "r"(addr));
}
__device__ __forceinline__ float bf_lo(uint32_t v) { return __uint_as_float(v << 16); }
__device__ __forceinline__ float bf_hi(uint32_t v) { return __uint_as_float(v & 0xffff0000u); }
__device__ __forceinline__ uint32_t ldg16(const bf16* p) {
  uint32_t v;
  asm volatile("ld.global.nc.u16 %0, [%1];" : "=r"(v) : "l"(p));
  return v;
}
__device__ __forceinline__ float2 cmul(float2 a, float2 b) { return make_float2(fmaf(a.x, b.x, -a.y * b.y), fmaf(a.x, b.y, a.y * b.x)); }
__device__ __forceinline__ float2 csqr(float2 a) { return make_float2(fmaf(a.x, a.x, -a.y * a.y), (a.x + a.x) * a.y); }
__device__ __forceinline__ float2 cexp2(float ar2, float ai) {
  float m;
  asm("ex2.approx.ftz.f32 %0, %1;" : "=f"(m) : "f"(ar2));
  const float k = fmaf(ai, 0.15915494f, 12582912.f) - 12582912.f;
  const float ph = fmaf(k, 1.7484555e-7f, fmaf(k, -6.2831855f, ai));
  return make_float2(m * __cosf(ph), m * __sinf(ph));
}
struct HC { __half2 re, im; };
__device__ __forceinline__ HC hmul(HC x, __half2 f) {
  const __half2 fr = __low2half2(f), fi = __high2half2(f);
  HC r;
  r.re = __hfma2(x.re, fr, __hmul2(__hneg2(x.im), fi));
  r.im = __hfma2(x.re, fi, __hmul2(x.im, fr));
  return r;
}
__device__ __forceinline__ uint32_t h_u32(__half2 v) { return *reinterpret_cast<uint32_t*>(&v); }
__device__ __forceinline__ void st_hc4(uint32_t a, const HC* v) {
  sts128u(a, h_u32(v[0].re), h_u32(v[1].re), h_u32(v[2].re), h_u32(v[3].re));
  sts128u(a + 128, h_u32(v[0].im), h_u32(v[1].im), h_u32(v[2].im), h_u32(v[3].im));
}
__device__ __forceinline__ uint32_t maxabs2(uint32_t a, uint32_t b) {
  uint32_t r;
  asm("max.xorsign.abs.bf16x2 %0, %1, %2;" : "=r"(r) : "r"(a), "r"(b));
  return r;
}
__device__ __forceinline__ float2 lds64f(uint32_t a) { float2 v; asm volatile("ld.shared.v2.f32 {%0,%1}, [%2];" : "=f"(v.x), "=f"(v.y) : "r"(a)); return v; }

constexpr int G1_STAGES = 3, G1_TX = 40960;
constexpr int SM_X = 0;
constexpr int SM_W = 49152;
constexpr int SM_SLAB = 122880;
constexpr int G2_TX = 28672, SM_W2 = 40960;
constexpr int SM_KT = 143360, KT_BYTES = 4096, KT_COPY = 1984;
constexpr int TB_K0 = 560, TB_E2 = 656, TB_O2 = 752, TB_E3 = 848, TB_O3 = 944;
constexpr int SM_WK = SM_KT + 5 * KT_BYTES;
constexpr int SM_U0 = SM_WK;
constexpr int U0_PL = 1184, U0_BYTES = 4 * U0_PL;
constexpr int X3_B = 544;
constexpr int XO_2E = 0, XO_2O = 3072, XO_3E = 6144, XO_3O = XO_3E + 4 * X3_B, XS_BYTES = XO_3O + 4 * X3_B;
constexpr int SM_XS = SM_U0 + 5 * U0_BYTES;
constexpr int KG_BYTES = 28672, KG_B = 16384;
constexpr int SM_KG3 = SM_WK, SM_KG2 = SM_XS + XS_BYTES;
constexpr int SM_AT = SM_W2 + 4 * 20480, SM_OUT = SM_W2;
constexpr int SM_MISC = SM_KG2 + KG_BYTES;
static_assert(SM_KG3 + KG_BYTES <= SM_KG2 && SM_XS + 3 * XS_BYTES <= SM_MISC && SM_MISC % 128 == 0, "smem");
static_assert(SM_W2 + 5 * 20480 <= SM_KT && SM_WK % 1024 == 0, "smem");
constexpr int SM_B1 = SM_MISC + 256;
constexpr int SM_B2 = SM_B1 + 384;
constexpr int SM_G = SM_B2 + 320;
constexpr int SM_TR = SM_MISC + 1280;
constexpr int SM_TOTAL = SM_MISC + 2304;
constexpr int SMEM_BYTES = SM_TOTAL + 1024;
static_assert(SMEM_BYTES <= 232448, "smem");

struct Params {
  const bf16 *u, *Are, *Aim, *Bre, *Bim, *Cre, *Cim, *logdt, *Dsk, *w1, *b1, *w2, *b2, *gate_w;
  const bf16* uT;
  bf16* w2p;
  unsigned *gate, *flag, *epoch;
};

__device__ __forceinline__ uint32_t u0_chunk(uint32_t u0, int q) { return u0 + (q & 3) * U0_PL + (q >> 2) * 16; }

__device__ __forceinline__ void build_x(uint32_t xs, uint32_t u0, int w4, int lane) {
#pragma unroll 1
  for (int m = 32 * w4 + lane - 1; m < 191; m += 128) {
    const uint2 c0 = lds64u(u0_chunk(u0, m - 1) + 8);
    const uint4 c1 = lds128u(u0_chunk(u0, m)), c2 = lds128u(u0_chunk(u0, m + 1));
    const uint32_t w[10] = {c0.x, c0.y, c1.x, c1.y, c1.z, c1.w, c2.x, c2.y, c2.z, c2.w};
    float s[18];
    s[0] = 0.f;
#pragma unroll
    for (int k = 0; k < 17; k++) s[k + 1] = s[k] + ((k & 1) ? bf_hi(w[k >> 1]) : bf_lo(w[k >> 1]));
#define WIN(hi, lo) pack_bf16(s[hi] - s[lo], s[hi + 1] - s[lo + 1]), pack_bf16(s[hi + 2] - s[lo + 2], s[hi + 3] - s[lo + 3]), \
                    pack_bf16(s[hi + 4] - s[lo + 4], s[hi + 5] - s[lo + 5]), pack_bf16(s[hi + 6] - s[lo + 6], s[hi + 7] - s[lo + 7])
    sts128u(xs + XO_2E + (m + 1) * 16, WIN(7, 2));
    sts128u(xs + XO_2O + (m + 1) * 16, WIN(10, 7));
    if (m <= 126) {
      const int i = m + 1, j = m + 2;
      sts128u(xs + XO_3O + (i & 1) * (2 * X3_B) + (i >> 6) * X3_B + ((i >> 1) & 31) * 16, WIN(8, 1));
      if (m <= 125) sts128u(xs + XO_3E + (j & 1) * (2 * X3_B) + (j >> 6) * X3_B + ((j >> 1) & 31) * 16, WIN(9, 0));
      else sts128u(xs + XO_3E, 0, 0, 0, 0);
    }
#undef WIN
  }
}

#define TQ(k)
template <int I0, int I1> __device__ __forceinline__ void load_tab(uint32_t a, uint32_t* R) {
#pragma unroll
  for (int i = I0; i < I1; i++) R[i] = lds32(a + 16 * i);
}
__device__ __forceinline__ void conv_far(uint32_t xs, uint32_t u0, uint32_t kt, int barid, int w4, int lane, uint32_t tq) {
  const int g = lane >> 2, c = lane & 3, o = 8 * w4 + g;
  const uint32_t ta = kt + (g & 1) * KT_COPY + ((g & 1) - o + 2 * c - 64) * 2;
  float a3[16], a2[24], b2[16];
  {
    uint32_t E[12], O[12];
    load_tab<4, 12>(ta + TB_E3 * 2, E);
    load_tab<4, 12>(ta + TB_O3 * 2, O);
    const float k1024 = bf_lo(lds16(kt + (TB_E2 - 63) * 2));
#pragma unroll
    for (int hf = 0; hf < 2; hf++) {
      const int x = 16 * o + 8 * hf + 2 * c;
      const uint32_t pa = u0_chunk(u0, (x - 4) >> 3) + ((x - 4) & 7) * 2, pb = u0_chunk(u0, (x - 2) >> 3) + ((x - 2) & 7) * 2;
#pragma unroll
      for (int b = 0; b < 2; b++) {
        const uint32_t va = lds32(pa + b * 256), vb = lds32(pb + b * 256);
        a3[8 * hf + 4 * b] = k1024 * (bf_lo(va) + bf_hi(va));
        a3[8 * hf + 4 * b + 1] = k1024 * (bf_hi(va) + bf_lo(vb));
        a3[8 * hf + 4 * b + 2] = 0.f;
        a3[8 * hf + 4 * b + 3] = 0.f;
      }
    }
    const uint64_t d3 = make_desc(xs + XO_3E, 128, X3_B, 0);
    asm volatile("" : R8(a3, 0), R8(a3, 8));
    TQ(0);
    named_bar(barid, 128);
    wg_fence();
    wgr32<1, 1>(a3, E[8], E[4], E[9], E[5], d3);
    wgr32<1, 1>(a3, E[10], E[6], E[11], E[7], d3 + 16);
    wgr32<1, 1>(a3, O[8], O[4], O[9], O[5], d3 + (4 * X3_B >> 4));
    wgr32<1, 1>(a3, O[10], O[6], O[11], O[7], d3 + (4 * X3_B >> 4) + 16);
    wg_commit();
  }
  TQ(1);
  const uint64_t d2 = make_desc(xs + XO_2E, 128, 512, 0);
  {
    uint32_t E[12];
    load_tab<0, 12>(ta + TB_E2 * 2, E);
    wg_fence();
    wgr48<0, 1>(a2, E[8], E[4], E[9], E[5], d2);
    wgr32<0, 1>(b2, E[0], 0u, E[1], 0u, d2);
    wgr48<1, 1>(a2, E[10], E[6], E[11], E[7], d2 + 16);
    wgr32<1, 1>(b2, E[2], 0u, E[3], 0u, d2 + 16);
    wg_commit();
  }
  TQ(2);
  wg_wait<1>();
  TQ(3);
  {
    uint32_t O[12];
    load_tab<0, 12>(ta + TB_O2 * 2, O);
    wg_fence();
    wgr48<1, 1>(a2, O[8], O[4], O[9], O[5], d2 + 192);
    wgr32<1, 1>(b2, O[0], 0u, O[1], 0u, d2 + 192);
    wgr48<1, 1>(a2, O[10], O[6], O[11], O[7], d2 + 192 + 16);
    wgr32<1, 1>(b2, O[2], 0u, O[3], 0u, d2 + 192 + 16);
    wg_commit();
  }
  named_bar(barid, 128);
  {
    const uint32_t pw = xs + XO_3E + ((16 * o + 2 * c) ^ (((g >> 1) & 1) << 3)) * 4;
#pragma unroll
    for (int hf = 0; hf < 2; hf++) {
      sts64f((pw ^ (hf * 32)), a3[8 * hf], a3[8 * hf + 1]);
      sts64f((pw ^ (hf * 32)) + 2048, a3[8 * hf + 4] + a3[8 * hf + 2], a3[8 * hf + 5] + a3[8 * hf + 3]);
    }
  }
  wg_wait<0>();
  float f2[12];
#pragma unroll
  for (int i = 0; i < 12; i++) {
    const int b = i >> 1, e = i & 1;
    f2[i] = a2[4 * b + e];
    if (b >= 1) f2[i] += a2[4 * b - 2 + e];
    if (b >= 2) f2[i] += b2[4 * b - 8 + e];
  }
  TQ(4);
  named_bar(barid, 128);
  TQ(5);
  const uint32_t pr = xs + XO_3E + ((8 * o + 2 * c) ^ ((g >> 2) << 3)) * 4, pw = xs + XO_2E + ((8 * o + 2 * c) ^ (w4 << 3)) * 4;
#pragma unroll
  for (int b = 0; b < 6; b++) {
    if (b >= 2) {
      const float2 v = lds64f(pr + (b - 2) * 1024);
      f2[2 * b] += v.x; f2[2 * b + 1] += v.y;
    }
    sts64f(pw + b * 1024, f2[2 * b], f2[2 * b + 1]);
  }
}
template <int S0, int S1> __device__ __forceinline__ void near_load(uint32_t ta, uint32_t* R) {
#pragma unroll
  for (int s = S0; s < S1; s++) {
    R[4 * (s - S0)] = s < 3 ? 0u : lds32(ta + 512 + 32 * s);
    R[4 * (s - S0) + 1] = lds32(ta + 32 * s);
    R[4 * (s - S0) + 2] = s < 3 ? 0u : lds32(ta + 512 + 32 * s + 16);
    R[4 * (s - S0) + 3] = lds32(ta + 32 * s + 16);
  }
}
template <int S0, int S1> __device__ __forceinline__ void near_mma(float* acc, const uint32_t* R, uint64_t d0) {
  wg_fence();
#pragma unroll
  for (int s = S0; s < S1; s++)
    wgr64(acc, R[4 * (s - S0)], R[4 * (s - S0) + 1], R[4 * (s - S0) + 2], R[4 * (s - S0) + 3], d0 + ((2 * s + 2) & 3) * (U0_PL >> 4) + ((2 * s + 6) >> 2));
  wg_commit();
}
__device__ __forceinline__ void conv_near(uint32_t xs, uint32_t u0, uint32_t kt, int barid, uint32_t dsk2, int w4, int lane, uint32_t tq) {
  const int g = lane >> 2, c = lane & 3, o = 8 * w4 + g;
  float acc[32];
  const uint32_t ta = kt + (g & 1) * KT_COPY + (TB_K0 + (g & 1) - o + 2 * c - 528) * 2;
  const uint64_t d0 = make_desc(u0 - 160, U0_PL, 128, 0);
  {
    uint32_t R[28], Q[24];
    near_load<0, 7>(ta, R);
    TQ(6);
    named_bar(barid, 128);
    TQ(7);
    const uint32_t pa = xs + XO_2E + ((o ^ (c << 3)) + 64 * c) * 4;
#pragma unroll
    for (int j = 0; j < 8; j++) {
      acc[4 * j] = j < 2 ? 0.f : lds32f(pa + (j - 2) * 1024);
      acc[4 * j + 1] = j < 2 ? 0.f : lds32f(pa + (j - 2) * 1024 + 128);
      acc[4 * j + 2] = 0.f;
      acc[4 * j + 3] = 0.f;
    }
    asm volatile("" : R8(acc, 0), R8(acc, 8), R8(acc, 16), R8(acc, 24));
    near_mma<0, 7>(acc, R, d0);
    near_load<7, 13>(ta, Q);
    near_mma<7, 13>(acc, Q, d0);
    TQ(8);
    wg_wait<0>();
    TQ(9);
  }
  {
    uint32_t R[24];
    near_load<13, 19>(ta, R);
    near_mma<13, 19>(acc, R, d0);
  }
  TQ(10);
  uint32_t uu[8];
  ldsm4t(u0 + w4 * U0_PL + lane * 16, uu);
  ldsm4t(u0 + w4 * U0_PL + lane * 16 + 512, uu + 4);
  named_bar(barid, 128);
  wg_wait<0>();
  TQ(11);
#pragma unroll
  for (int j = 0; j < 8; j++) {
    float x = acc[4 * j], y = acc[4 * j + 1];
    if (j) { x += acc[4 * j - 2]; y += acc[4 * j - 1]; }
    uu[j] = as_u32(__hadd2_rn(as_bf162(pack_bf16(x, y)), __hmul2_rn(as_bf162(uu[j]), as_bf162(dsk2))));
  }
  const uint32_t oa = kt + (lane >> 1) * 128 + (((4 * (lane & 1) + w4) ^ ((lane >> 1) & 7)) << 4);
  stsm_x4_t(oa, uu[0], uu[1], uu[2], uu[3]);
  stsm_x4_t(oa + 2048, uu[4], uu[5], uu[6], uu[7]);
}

__device__ __forceinline__ void kt_put(uint32_t a, uint32_t v) {
  sts16(a, v);
  sts16(a + KT_COPY + 2, v);
}
__device__ __forceinline__ void kt_store(uint32_t kt, int r0, int c, const float* kv, float scale, int d) {
  const uint32_t a0 = kt + (TB_K0 - 8 * r0 - (((c & 1) << 1) | (c >> 1))) * 2;
  const uint32_t a1 = kt + (c < 2 ? TB_K0 - 256 - 8 * r0 - 2 * c : TB_E2 + 1 - 32 * (c - 2) - r0) * 2;
  const int s1r = c < 2 ? 128 : 16, s1e = c < 2 ? -8 : (TB_O2 - TB_E2 - 1) * 2;
  const uint32_t a2 = kt + (((r0 & 1) ? TB_O3 : TB_E3 + 1) - 32 * c - (r0 >> 1)) * 2;
#pragma unroll
  for (int i = 0; i < 12; i++) {
    const int h = (i >> 1) & 1, e = i & 1;
    const float val = kv[i] * scale;
    const uint32_t v = pack_bf16(val, 0.f);
    if (i < 4) kt_put(a0 - 128 * h - 8 * e, v);
    else if (i < 8) {
      uint32_t a = a1 - s1r * h + s1e * e;
      bool wide = c == 0;
      if (i == 4 && c == 2 && r0 == 0) {
        a = kt + (TB_K0 - 512) * 2;
        wide = true;
        kt_put(a - 4, v);
      }
      kt_put(a, v);
      if (wide) {
        kt_put(a - 2, v);
        if (i != 4 || r0 != 0 || c != 0) kt_put(a + 2, v);
      }
    } else {
      uint32_t a = a2 - 8 * h - 32 * e;
      if (i == 8 && c == 0 && r0 == 0) a = kt + (TB_E2 - 63) * 2;
      if (c < 2 || (i == 8 && c == 2 && r0 == 0)) kt_put(a, v);
    }
  }
}

__global__ void __cluster_dims__(2, 1, 1) __launch_bounds__(512, 1)
fused_kernel(const __grid_constant__ CUtensorMap tm_x, const __grid_constant__ CUtensorMap tm_w1,
             const __grid_constant__ CUtensorMap tm_slab, const __grid_constant__ CUtensorMap tm_ut,
             const __grid_constant__ CUtensorMap tm_hst, const __grid_constant__ CUtensorMap tm_hld,
             const __grid_constant__ CUtensorMap tm_w2, const __grid_constant__ CUtensorMap tm_aT,
             const __grid_constant__ CUtensorMap tm_ast, const __grid_constant__ CUtensorMap tm_out, const Params p) {
  extern __shared__ uint8_t smem_raw[];
  const uint32_t sraw = smem_u32(smem_raw);
  const uint32_t sb = (sraw + 1023) & ~1023u;
  const int tid = threadIdx.x, warp = __shfl_sync(0xffffffffu, tid >> 5, 0), lane = tid & 31;
  const int cta = blockIdx.x, cl = cta >> 1, rk = cta & 1;
  const int idx = (cl & 7) * 8 + (cl >> 3);
  const int sl = (idx & 3) + ((idx >> 3) & 1) * 4, tt = 2 * (((idx >> 2) & 1) + (idx >> 4) * 2) + rk;
  const int dq = idx & 3, T2 = 2 * (idx >> 2) + rk;
  const uint32_t bar_full1 = sb + SM_MISC;
  const uint32_t bar_empty1 = bar_full1 + 24;
  const uint32_t bar_emptyx = bar_empty1 + 24;
  const uint32_t bar_full2 = bar_emptyx + 24;
  const uint32_t bar_empty2 = bar_full2 + 40;
  const uint32_t bar_ring = bar_empty2 + 40;
  const uint32_t bar_at = bar_ring + 8;
  const uint32_t bar_fin = bar_at + 8;
  const uint32_t bar_par = bar_fin + 8;
  const uint32_t bar_slab = bar_par + 8;
  const uint32_t bar_u = bar_slab + 8;
  const uint32_t bar_k4 = bar_u + 8;
  const uint32_t peer_off = mapa(sb, rk ^ 1) - sb;

  if (tid == 32) {
    for (int i = 0; i < G1_STAGES; i++) mbar_init(bar_full1 + 8 * i, 1);
    asm volatile("fence.mbarrier_init.release.cluster;" ::: "memory");
    mbar_expect_tx(bar_full1, G1_TX);
    tma_load2d(sb + SM_X, &tm_x, 0, tt * 128, bar_full1);
    tma_load3d(sb + SM_W, &tm_w1, 0, 0, sl * 3, bar_full1);
    tma_load3d(sb + SM_W + 12288, &tm_w1, 0, 32, sl * 3, bar_full1);
  }
  if (warp == 8) {
    if (lane == 0) {
      mbar_init(bar_par, 1);
      asm volatile("fence.mbarrier_init.release.cluster;" ::: "memory");
      mbar_expect_tx(bar_par, 11520 + 384 + 320);
    }
    __syncwarp();
    const int a = lane / 5, ch = lane - 5 * a;
    const bf16* pp = (a == 0 ? p.Are : a == 1 ? p.Aim : a == 2 ? p.Bre : a == 3 ? p.Bim : a == 4 ? p.Cre : p.Cim) + (5 * cta + ch) * NM_;
    uint32_t dst = sb + SM_KT + ch * KT_BYTES + a * 384, bytes = 384;
    if (lane == 30) { pp = p.b1 + sl * 192; dst = sb + SM_B1; }
    if (lane == 31) { pp = p.b2 + dq * 160; dst = sb + SM_B2; bytes = 320; }
    bulk_load(dst, pp, bytes, bar_par);
  }
  if (tid == 96) {
    for (int i = 0; i < G1_STAGES; i++) { mbar_init(bar_empty1 + 8 * i, 16); mbar_init(bar_emptyx + 8 * i, 8); }
    for (int i = 0; i < 5; i++) { mbar_init(bar_full2 + 8 * i, 1); mbar_init(bar_empty2 + 8 * i, 8); }
    mbar_init(bar_ring, 18);
    mbar_init(bar_at, 2);
    mbar_init(bar_fin, 4);
    mbar_init(bar_slab, 1);
    mbar_init(bar_u, 1);
    mbar_init(bar_k4, 4);
    asm volatile("fence.mbarrier_init.release.cluster;" ::: "memory");
  }
  cluster_arrive();
  cluster_wait();

  const int wg = warp >> 2, w4 = warp & 3, g = lane >> 2, c = lane & 3;
  const unsigned ep1 = p.epoch[cta] + 1;
  if (warp < 8) {
    float acc[96];
#pragma unroll
    for (int i = 0; i < 96; i++) acc[i] = 0.f;
    if (tid == 32) {
#pragma unroll
      for (int kb = 1; kb < G1_STAGES; kb++)
        tma_load3d_mc(sb + SM_W + kb * 24576 + rk * 12288, &tm_w1, 0, kb * 64 + rk * 32, sl * 3, bar_full1 + 8 * kb);
    }
    if (tid == 128) {
#pragma unroll
      for (int kb = 1; kb < G1_STAGES; kb++) {
        mbar_expect_tx(bar_full1 + 8 * kb, G1_TX);
        tma_load2d(sb + SM_X + kb * 16384, &tm_x, kb * 64, tt * 128, bar_full1 + 8 * kb);
      }
    }
    if (tid == 64) { prefetch_tmap(&tm_hst); prefetch_tmap(&tm_hld); prefetch_tmap(&tm_w2); prefetch_tmap(&tm_ut); }
    if (tid == 96) { prefetch_tmap(&tm_aT); prefetch_tmap(&tm_ast); prefetch_tmap(&tm_out); prefetch_tmap(&tm_slab); }
    __syncwarp();
    {
      const uint64_t da0 = make_desc(sb + SM_X + wg * 8192, 16, 1024, 1);
      const uint64_t db0 = make_desc(sb + SM_W, 4096, 1024, 1);
      const uint32_t rel = bar_empty1 + (lane == 1 ? peer_off : lane * 12);
      if (wg) named_arrive(6, 256);
#pragma unroll
      for (int kb = 0; kb < 10; kb++) {
        const int so = kb % 3, ph = (kb / 3) & 1;
        mbar_wait(bar_full1 + so * 8, ph);
        if (tid == 0 && kb == 0) TS(1);
        const uint64_t da = da0 + so * (16384 >> 4), db = db0 + so * (24576 >> 4);
        named_bar(6 + wg, 256);
        if ((tid & 127) == 0) TR(16 * wg + kb);
        wg_fence();
#pragma unroll
        for (int k = 0; k < 4; k++) wgmma_n192(acc, da + k * 2, db + (k >> 1) * 768 + (k & 1) * 128);
        wg_commit();
        if (kb < 9 || !wg) named_arrive(7 - wg, 256);
        if (tid == 128) TR(160 + kb);
        wg_wait<0>();
        if (tid == 128) TR(176 + kb);
        if (kb < 7 && lane < 3) mbar_arrive_cluster(rel + so * 8);
        if (kb < 7 && warp == 4) {
          mbar_wait(bar_emptyx + so * 8, ph);
          if (lane == 0) {
            mbar_expect_tx(bar_full1 + so * 8, G1_TX);
            tma_load2d(sb + SM_X + so * 16384, &tm_x, (kb + 3) * 64, tt * 128, bar_full1 + so * 8);
            TR(192 + kb);
          }
          __syncwarp();
        }
        if (kb < 7 && warp == 5) {
          if (lane == 0) TR(208 + kb);
          mbar_wait(bar_empty1 + so * 8, ph);
          if (lane == 0) {
            tma_load3d_mc(sb + SM_W + so * 24576 + rk * 12288, &tm_w1, 0, (kb + 3) * 64 + rk * 32, sl * 3, bar_full1 + so * 8);
            TR(224 + kb);
          }
          __syncwarp();
        }
      }
    }
    mbar_wait(bar_par, 0);
    if (tid == 0) TS(3);
    const int mrow = w4 * 16 + (lane & 7) + ((lane >> 3) & 1) * 8;
    const bf162 one2 = __float2bfloat162_rn(1.f);
#pragma unroll
    for (int j = 0; j < 24; j += 2) {
      uint32_t r[4];
#pragma unroll
      for (int q = 0; q < 4; q++) {
        const int jj = j + (q >> 1);
        bf162 v = as_bf162(pack_bf16(acc[4 * jj + 2 * (q & 1)], acc[4 * jj + 2 * (q & 1) + 1]));
        v = __hfma2_relu(v, one2, as_bf162(lds32(sb + SM_B1 + jj * 16 + c * 4)));
        r[q] = as_u32(__hmul2_rn(v, v));
      }
      const int chunk = (j & 7) + (lane >> 4);
      stsm_x4(sb + SM_X + (j >> 3) * 16384 + wg * 8192 + mrow * 128 + ((chunk ^ (mrow & 7)) << 4), r[0], r[1], r[2], r[3]);
      if ((j & 7) == 6) {
        if (tid == 0) TR(10 + 2 * (j >> 3));
        fence_async_smem();
        __syncwarp();
        if (tid == 0) TR(11 + 2 * (j >> 3));
        if (lane == 0) tma_store2d(&tm_hst, sb + SM_X + (j >> 3) * 16384 + warp * 2048, 0, (sl * 3 + (j >> 3)) * L_ + tt * 128 + warp * 16);
      }
    }
    if (lane == 0) {
      bulk_commit();
      if (tid == 0) TS(4);
      bulk_wait_read0();
      mbar_arrive(bar_ring);
      mbar_arrive_cluster(bar_ring + peer_off);
      bulk_wait<0>();
      red_relaxed_add(p.flag + ((2 * tt + wg) * 8 + sl) * 8, 1);
      if (tid == 0) TS(5);
    }
    __syncwarp();
  } else {
    const int wgs = wg & 1, gam = w4 >> 1, slot = (w4 & 1) * 32 + lane;
    const uint32_t ldt[2] = {ldg16(p.logdt + 5 * cta + 2 * wgs + gam), ldg16(p.logdt + 5 * cta + 4)};
    const uint32_t kgA = sb + (wgs ? SM_KG3 : SM_KG2);
    const uint32_t ksa = kgA + gam * 8192 + (slot >> 3) * 256 + (slot & 7) * 16, ksb = ksa + KG_B - gam * 2048;
    const uint64_t dka = make_desc(kgA, 128, 2048, 0), dkb = make_desc(kgA + KG_B, 128, 2048, 0);
    const uint32_t kt0 = sb + SM_KT + (2 * wgs + gam) * KT_BYTES, kt4 = sb + SM_KT + 4 * KT_BYTES;
    unsigned ucnt = 0;
    mbar_wait(bar_par, 0);
    if (tid == 256) TS(14);
    if (tid == 448) {
      mbar_expect_tx(bar_slab, 20480);
      tma_load2d(sb + SM_SLAB, &tm_slab, sl * 80, tt * 128, bar_slab);
    }
    if (tid == 480 && tt < 14) tma_pf3d(&tm_w1, 0, 192 + tt * 32, sl * 3);
    __syncwarp();
    float dts[2], css[2], scs[2];
#pragma unroll
    for (int j = 0; j < 2; j++) {
      const uint32_t kt = j ? kt4 : kt0;
      uint32_t mx[2];
#pragma unroll
      for (int i = 0; i < 2; i++) {
        const uint2 a = lds64u(kt + 768 + 768 * i + lane * 8), b = lds64u(kt + 1024 + 768 * i + lane * 8), d = lds64u(kt + 1280 + 768 * i + lane * 8);
        const uint32_t m = maxabs2(maxabs2(maxabs2(a.x, a.y), maxabs2(b.x, b.y)), maxabs2(d.x, d.y));
        mx[i] = min(max(__reduce_max_sync(0xffffffffu, max((m << 16) & 0x7f800000u, m & 0x7f800000u)), 64u << 23), 190u << 23);
      }
      dts[j] = __bfloat162float(__float2bfloat16_rn(expf(bf_lo(ldt[j]))));
      css[j] = __uint_as_float((254u << 23) - mx[0]) * __uint_as_float((254u << 23) - mx[1]);
      scs[j] = dts[j] * __uint_as_float(mx[0]) * __uint_as_float(mx[1]);
    }
    float acc[24], dt = dts[0], cs = css[0];
#pragma unroll
    for (int i = 0; i < 24; i++) acc[i] = 0.f;
    uint32_t po = kt0 + slot * 2;
#define PIN2(v) asm volatile("" : "+f"((v).x), "+f"((v).y))
#define PIN(v) asm volatile("" : "+r"(*reinterpret_cast<uint32_t*>(&(v).re)), "+r"(*reinterpret_cast<uint32_t*>(&(v).im)))
#pragma unroll 1
    for (int s = 0; s < (wgs ? 3 : 5); s++) {
      if ((tid & 127) == 0) TR(64 + 20 * wgs + 4 * s);
      wg_fence();
      wgmma_n48_tt(acc, dka, dkb, s != 1 && s != 4);
      wgmma_n48_tt(acc, dka + 16, dkb + 16, 1);
      float ar2 = dt * 1.4426950409f * bf_lo(lds16(po)), ai = dt * bf_lo(lds16(po + 384));
      float2 cc = cmul(make_float2(bf_lo(lds16(po + 1536)), bf_lo(lds16(po + 1920))), make_float2(bf_lo(lds16(po + 768)), bf_lo(lds16(po + 1152))));
      cc.x *= cs; cc.y *= cs;
      float2 e1 = cexp2(ar2, ai);
      PIN2(e1); PIN2(cc);
      wgmma_n48_tt(acc, dka + 32, dkb + 32, 1);
      wgmma_n48_tt(acc, dka + 48, dkb + 48, 1);
      asm volatile("" : "+f"(ar2), "+f"(ai));
      float2 e64 = cexp2(64.f * ar2, 64.f * ai);
      const float2 e2 = csqr(e1), e4 = csqr(e2);
      float2 e8 = csqr(e4), c4 = cmul(cc, e4);
      PIN2(e64); PIN2(e8); PIN2(c4);
      wgmma_n48_tt(acc, dka + 64, dkb + 64, 1);
      wgmma_n48_tt(acc, dka + 80, dkb + 80, 1);
      PIN2(e64); PIN2(e8);
      const float2 e16 = csqr(e8), e128 = csqr(e64), h1 = csqr(e128), h2 = csqr(h1);
      float2 e32 = csqr(e16), h4 = csqr(h2);
      PIN2(e32); PIN2(h4);
      wgmma_n48_tt(acc, dka + 96, dkb + 96, 1);
      wgmma_n48_tt(acc, dka + 112, dkb + 112, 1);
      wg_commit();
      if ((tid & 127) == 0) TR(64 + 20 * wgs + 4 * s + 1);
      HC va[8], vb[8];
      const __half2 g32 = __floats2half2_rn(e32.x, -e32.y), g64 = __floats2half2_rn(e64.x, -e64.y), g128 = __floats2half2_rn(e128.x, -e128.y);
      const __half2 f1 = __floats2half2_rn(e1.x, e1.y), fh1 = __floats2half2_rn(h1.x, h1.y), fh2 = __floats2half2_rn(h2.x, h2.y);
      const __half2 fh4 = __floats2half2_rn(h4.x, h4.y);
      va[0].re = __floats2half2_rn(1.f, e8.x); va[0].im = __floats2half2_rn(0.f, -e8.y);
      va[1] = hmul(va[0], __floats2half2_rn(e16.x, -e16.y));
      vb[0].re = __floats2half2_rn(cc.x, c4.x); vb[0].im = __floats2half2_rn(cc.y, c4.y);
      vb[1] = hmul(vb[0], __floats2half2_rn(e2.x, e2.y));
      va[2] = hmul(va[0], g32); va[3] = hmul(va[1], g32);
      vb[2] = hmul(vb[0], f1); vb[3] = hmul(vb[1], f1);
      PIN(va[2]); PIN(va[3]); PIN(vb[2]); PIN(vb[3]);
      if (s == 3) {
        const uint32_t za = sb + SM_KT + (tid & 127) * 16;
        sts128u(za, 0, 0, 0, 0); sts128u(za + 2048, 0, 0, 0, 0); sts128u(za + 4096, 0, 0, 0, 0); sts128u(za + 6144, 0, 0, 0, 0);
      }
      if ((tid & 127) == 0) TR(64 + 20 * wgs + 4 * s + 2);
      wg_wait<0>();
      named_bar(1 + wg, 128);
      if ((tid & 127) == 0) TR(64 + 20 * wgs + 4 * s + 3);
      st_hc4(ksa, va);
      PIN(va[0]);
#pragma unroll
      for (int i = 0; i < 4; i++) va[4 + i] = hmul(va[i], g64);
      st_hc4(ksb, vb);
      PIN(va[0]);
#pragma unroll
      for (int i = 0; i < 4; i++) va[i] = hmul(va[i], g128);
      st_hc4(ksa + 2048, va + 4);
      PIN(va[4]);
#pragma unroll
      for (int i = 4; i < 8; i++) va[i] = hmul(va[i], g128);
      st_hc4(ksa + 4096, va);
      PIN(vb[0]);
      vb[4] = hmul(vb[0], fh1); vb[5] = hmul(vb[1], fh1);
      vb[6] = hmul(vb[0], fh2); vb[7] = hmul(vb[4], fh2);
      st_hc4(ksa + 6144, va + 4);
      PIN(vb[0]);
      vb[0].re = __lows2half2(vb[0].re, vb[4].re); vb[0].im = __lows2half2(vb[0].im, vb[4].im);
      vb[0] = hmul(vb[0], fh4);
      vb[1] = hmul(vb[0], fh2);
      vb[2] = hmul(vb[1], fh2);
      st_hc4(ksb + 2048, vb + 4);
      st_hc4(ksb + 4096, vb);
      po += 128;
      if (s == 2) { po = kt4 + (96 * gam + slot) * 2; dt = dts[1]; cs = css[1]; }
      if (wgs) {
        if (s == 0) {
          if (tid == 384) TR(240);
          mbar_wait(bar_slab, 0);
          if (tid == 384) TR(241);
          uint32_t r[40];
#pragma unroll
          for (int j = 0; j < 10; j++) ldsm4t(sb + SM_SLAB + (32 * w4 + lane) * 160 + j * 16, r + 4 * j);
          named_bar(4, 128);
          const uint32_t o = sb + SM_SLAB + (lane >> 3) * 5120 + (lane & 7) * 64 + ((w4 ^ ((lane >> 1) & 3)) << 4);
#pragma unroll
          for (int j = 0; j < 10; j++) stsm_x4(o + j * 512, r[4 * j], r[4 * j + 1], r[4 * j + 2], r[4 * j + 3]);
        } else if (tid == 416) {
          if (s == 1) {
            TR(242);
            bulk_wait<0>();
            TR(243);
            red_relaxed_add(p.flag + (260 + sl) * 8, 1);
            mbar_expect_tx(bar_slab, 15360);
#pragma unroll
            for (int i = 0; i < 3; i++) tma_load3d(sb + SM_SLAB + i * 5120, &tm_w2, 0, (3 * (cta & 31) + i) * 16, (cta >> 5) * 5, bar_slab);
            TS(16);
          } else {
            TR(244);
            mbar_wait(bar_slab, 1);
            TR(245);
            bulk_store(p.w2p + cta * 7680, sb + SM_SLAB, 15360);
            bulk_commit();
          }
        }
        if (tid == 480 && s == 0) l2_prefetch(p.w2 + (size_t)cta * 7680, 15360);
        if (warp == 14 && s == 1 && lane < 20) l2_prefetch(p.uT + (20 * cta + lane) * 592, 160);
        if (tid == 384 && s == 2) ucnt = ld_relaxed(p.flag + (260 + (cta >> 4)) * 8);
      }
      fence_async_smem();
      named_bar(1 + wg, 128);
      if (s == 0 && tid == 416) {
        tma_store3d(&tm_ut, sb + SM_SLAB, 80 + 32 * tt, 80 * sl, 0);
        bulk_commit();
      }
      if (s == 3) {
        float kv[12];
#pragma unroll
        for (int i = 0; i < 12; i++) kv[i] = gam ? acc[12 + i] : acc[i];
        kt_store(kt0, 16 * (w4 & 1) + g, c, kv, scs[0], 5 * cta + gam);
        if (tid == 256) TS(15);
      }
      __syncwarp();
    }
    wg_fence();
#pragma unroll
    for (int ks = 0; ks < 4; ks++) wgmma_n48_tt(acc, dka + ks * 16, dkb + ks * 16, 1);
    if (wgs) {
#pragma unroll
      for (int ks = 4; ks < 8; ks++) wgmma_n48_tt(acc, dka + ks * 16, dkb + ks * 16, 1);
    }
    wg_commit();
    {
      const uint32_t za = sb + SM_KT + (wgs ? 2 : 4) * KT_BYTES + (tid & 127) * 16;
      sts128u(za, 0, 0, 0, 0); sts128u(za + 2048, 0, 0, 0, 0);
      if (wgs) { sts128u(za + 4096, 0, 0, 0, 0); sts128u(za + 6144, 0, 0, 0, 0); }
    }
    if (tid == 384) TR(246);
    wg_wait<0>();
    named_bar(1 + wg, 128);
    if (tid == 384) {
      TR(247);
#pragma unroll 1
      for (int it = 0; (int)(ucnt - 16 * ep1) < 0; ++it) {
        ucnt = ld_relaxed(p.flag + (260 + (cta >> 4)) * 8);
        if (it > SPIN_LIMIT) SPIN_FAIL;
      }
      mbar_expect_tx(bar_u, 5 * U0_BYTES);
      bulk_load(sb + SM_U0, p.uT + cta * (5 * 2368), 5 * U0_BYTES, bar_u);
      TS(17);
      TR(248);
    }
    if (tid == 416) {
      bulk_wait<0>();
      red_relaxed_add(p.flag + (268 + (cta >> 5)) * 8, 1);
      mbar_arrive(bar_ring);
      mbar_arrive_cluster(bar_ring + peer_off);
      TS(19);
    }
    __syncwarp();
    float kv[12];
#pragma unroll
    for (int i = 0; i < 12; i++) kv[i] = gam ? acc[12 + i] : acc[i];
    if (!wgs) {
      const uint32_t xa = kgA + ((w4 & 1) * 32 + lane) * 48;
      if (gam) {
        sts128f(xa, kv[0], kv[1], kv[2], kv[3]); sts128f(xa + 16, kv[4], kv[5], kv[6], kv[7]); sts128f(xa + 32, kv[8], kv[9], kv[10], kv[11]);
      }
      named_bar(1 + wg, 128);
      if (!gam) {
#pragma unroll
        for (int i = 0; i < 3; i++) {
          const float4 o = lds128f(xa + 16 * i);
          kv[4 * i] += o.x; kv[4 * i + 1] += o.y; kv[4 * i + 2] += o.z; kv[4 * i + 3] += o.w;
        }
      }
    }
    if (wgs || !gam) kt_store(wgs ? kt0 : kt4, 16 * (w4 & 1) + g, c, kv, wgs ? scs[0] : scs[1], 5 * cta + (wgs ? 2 + gam : 4));
    if (tid == 256) TS(18);
    named_bar(1 + wg, 128);
    if (!wgs && lane == 0) mbar_arrive(bar_k4);
    mbar_wait(bar_u, 0);
    if (tid == 384) TS(20);
#pragma unroll 1
    for (int ch = 2 * wgs; ch < 2 + 3 * wgs; ch++) {
      int ln = lane;
      asm volatile("" : "+r"(ln));
      const uint32_t xs = sb + SM_XS + (3 - wg) * XS_BYTES, u0 = sb + SM_U0 + ch * U0_BYTES + 160, kt = sb + SM_KT + ch * KT_BYTES;
      const uint32_t dk = ldg16(p.Dsk + 5 * cta + ch);
      const uint32_t tq = tid == 384 ? sb + SM_TR + 512 + (ch & 1) * 64 : 0u;
      if ((tid & 127) == 0) TR(32 + wgs * 16 + 2 * (ch - 2 * wgs));
      build_x(xs, u0, w4, ln);
      fence_async_smem();
      if (ch == 4) mbar_wait(bar_k4, 0);
      conv_far(xs, u0, kt, 1 + wg, w4, ln, tq);
      if ((tid & 127) == 0) TR(32 + wgs * 16 + 2 * (ch - 2 * wgs) + 1);
      conv_near(xs, u0, kt, 1 + wg, dk | (dk << 16), w4, ln, tq);
      fence_async_smem();
      named_bar(1 + wg, 128);
      if ((tid & 127) == 0) {
        tma_store2d(&tm_ast, kt, 0, (5 * cta + ch) * 32);
        bulk_commit();
      }
      __syncwarp();
    }
    if ((tid & 127) == 0) {
      TR(32 + wgs * 16 + 8);
      bulk_wait<0>();
      red_relaxed_add(p.flag + (256 + (cta >> 5)) * 8, 2 + wgs);
      TS(20 + wg);
    }
  }

  if (wg == 0) {
    float acc[80];
#pragma unroll
    for (int i = 0; i < 80; i++) acc[i] = 0.f;
    {
      const uint64_t da0 = make_desc(sb, 16, 1024, 1);
      const uint64_t db0 = make_desc(sb + SM_W2, 1024, 512, 2);
      const uint32_t rel = bar_empty2 + (lane ? peer_off : 0u);
      uint32_t so = 0, ph = 0, prev = 0;
#pragma unroll 1
      for (int kb = 0; kb < 24; kb++) {
        mbar_wait(bar_full2 + so * 8, ph);
        if (tid == 0 && kb == 0) TS(7);
        if (tid == 0 && kb == 12) TS(8);
        if (tid == 0) TR(96 + kb);
        const uint64_t da = da0 + so * (8192 >> 4), db = db0 + so * (20480 >> 4);
        wg_fence();
#pragma unroll
        for (int k = 0; k < 4; k++) wgmma_n160(acc, da + k * 2, db + k * 320);
        wg_commit();
        if (kb > 0 && kb <= 20) {
          wg_wait<1>();
          if (kb == 20) {
            if (lane == 0) mbar_arrive(bar_fin);
          } else if (lane < 2) mbar_arrive_cluster(rel + prev * 8);
        }
        prev = so;
        if (++so == 5) { so = 0; ph ^= 1; }
      }
    }
    wg_wait<0>();
    if (tid == 0) TS(9);
    named_bar(1, 128);
    mbar_wait(bar_at, 0);
    if (tid == 0) TS(11);
    const bf162 one2 = __float2bfloat162_rn(1.f);
    const bf162 ga = as_bf162(lds32(sb + SM_G + (w4 * 16 + g) * 4)), gb = as_bf162(lds32(sb + SM_G + (w4 * 16 + g + 8) * 4));
    const bf162 na = __hsub2_rn(one2, ga), nb = __hsub2_rn(one2, gb);
    const uint32_t al = sb + SM_AT + ((lane >> 4) * 8 + (lane & 7)) * 128 + (((2 * w4 + ((lane >> 3) & 1)) ^ (lane & 7)) << 4);
    const uint32_t ol = sb + SM_OUT + w4 * 5120 + (lane & 15) * 64;
#pragma unroll
    for (int j = 0; j < 20; j += 2) {
      uint32_t a[4], r[4];
      ldsm4t(al + j * 1024, a);
#pragma unroll
      for (int q = 0; q < 4; q++) {
        const int jj = j + (q >> 1);
        bf162 v = as_bf162(pack_bf16(acc[4 * jj + 2 * (q & 1)], acc[4 * jj + 2 * (q & 1) + 1]));
        v = __hadd2_rn(v, as_bf162(lds32(sb + SM_B2 + jj * 16 + c * 4)));
        v = __hmul2_rn(v, (q & 1) ? nb : na);
        r[q] = as_u32(__hadd2_rn(__hmul2_rn(as_bf162(a[q]), (q & 1) ? gb : ga), v));
      }
      stsm_x4(ol + (j >> 2) * 1024 + ((((j & 2) + (lane >> 4)) ^ ((lane >> 1) & 3)) << 4), r[0], r[1], r[2], r[3]);
    }
    fence_async_smem();
    __syncwarp();
    if (lane == 0) {
      tma_store3d(&tm_out, sb + SM_OUT + w4 * 5120, 0, T2 * 64 + w4 * 16, dq * 5);
      bulk_commit();
      if (tid == 0) p.epoch[cta] = ep1;
      bulk_wait_read0();
      if (tid == 0) TS(10);
    }
  } else if (warp == 4) {
    if (lane == 0) {
#pragma unroll 1
      for (int it = 0; (int)(ld_relaxed(p.flag + (268 + dq) * 8) - 32 * ep1) < 0; ++it) {
        if (it > SPIN_LIMIT) SPIN_FAIL;
      }
      mbar_wait(bar_ring, 0);
      const bf16* src = p.w2p + dq * (24 * 10240) + rk * 5120;
      uint32_t so = 0, ph = 1;
#pragma unroll 1
      for (int kb = 0; kb < 24; kb++, src += 10240) {
        if (kb >= 5) mbar_wait(bar_empty2 + so * 8, ph);
        mbar_expect_tx(bar_full2 + so * 8, G2_TX);
        bulk_load_mc(sb + SM_W2 + so * 20480 + rk * 10240, src, 10240, bar_full2 + so * 8);
        if (++so == 5) { so = 0; ph ^= 1; }
      }
    }
  } else if (warp == 5) {
    const unsigned* fl = p.flag + (T2 * 8 + (lane & 7)) * 8;
    unsigned rdy = 0;
    uint32_t so = 0, ph = 1;
    mbar_wait(bar_ring, 0);
#pragma unroll 1
    for (int kb = 0; kb < 24; kb++) {
#pragma unroll 1
      for (int it = 0; !((rdy >> (kb / 3)) & 1); ++it) {
        rdy = __ballot_sync(0xffffffffu, (int)(ld_relaxed(fl) - 4 * ep1) >= 0);
        if (it > SPIN_LIMIT) SPIN_FAIL;
      }
      if (lane == 0) {
        if (kb == 0) TS(6);
        if (kb >= 5) mbar_wait(bar_empty2 + so * 8, ph);
        tma_load2d(sb + so * 8192, &tm_hld, 0, kb * L_ + T2 * 64, bar_full2 + so * 8);
      }
      __syncwarp();
      if (++so == 5) { so = 0; ph ^= 1; }
    }
  } else if (wg == 1) {
#pragma unroll 1
    for (int r = 0; r < 2; r++) {
      const int t = T2 * 64 + dq * 16 + (w4 & 1) * 8 + r * 4 + (lane >> 3);
      const uint4* xr = (const uint4*)(p.u + (size_t)t * D_) + (lane & 7);
      const uint4* gw = (const uint4*)p.gate_w + (lane & 7);
      uint4 xv[10], gv[10];
#pragma unroll
      for (int i = 0; i < 10; i++) { xv[i] = __ldg(xr + 8 * i); gv[i] = __ldg(gw + 8 * i); }
      float s0 = 0.f, s1 = 0.f;
#pragma unroll
      for (int i = 0; i < 10; i++) {
        const uint32_t a = as_u32(__hmul2_rn(as_bf162(xv[i].x), as_bf162(gv[i].x))), b = as_u32(__hmul2_rn(as_bf162(xv[i].y), as_bf162(gv[i].y)));
        const uint32_t d = as_u32(__hmul2_rn(as_bf162(xv[i].z), as_bf162(gv[i].z))), e = as_u32(__hmul2_rn(as_bf162(xv[i].w), as_bf162(gv[i].w)));
        s0 += (bf_lo(a) + bf_hi(a)) + (bf_lo(b) + bf_hi(b));
        s1 += (bf_lo(d) + bf_hi(d)) + (bf_lo(e) + bf_hi(e));
      }
      s0 += s1;
#pragma unroll
      for (int o = 4; o; o >>= 1) s0 += __shfl_xor_sync(0xffffffffu, s0, o);
      if ((lane & 7) == 0) {
        const float z = __bfloat162float(__float2bfloat16_rn(s0));
        st_relaxed(p.gate + t, (ep1 << 16) | (pack_bf16(1.f / (1.f + __expf(-z)), 0.f) & 0xffffu));
      }
    }
    if (warp == 6) {
      unsigned v0 = 0, v1 = 0;
#pragma unroll 1
      for (int it = 0;; ++it) {
        v0 = ld_relaxed(p.gate + T2 * 64 + lane);
        v1 = ld_relaxed(p.gate + T2 * 64 + 32 + lane);
        if (__all_sync(0xffffffffu, ((v0 ^ (ep1 << 16)) | (v1 ^ (ep1 << 16))) < 65536u)) break;
        __nanosleep(200);
        if (it > SPIN_LIMIT) SPIN_FAIL;
      }
      sts32(sb + SM_G + lane * 4, __byte_perm(v0, 0, 0x1010));
      sts32(sb + SM_G + 128 + lane * 4, __byte_perm(v1, 0, 0x1010));
      __syncwarp();
      if (lane == 0) mbar_arrive(bar_at);
    } else if (lane == 0) {
      mbar_wait(bar_u, 0);
      mbar_wait(bar_fin, 0);
#pragma unroll 1
      for (int it = 0; (int)(ld_relaxed(p.flag + (256 + dq) * 8) - 160 * ep1) < 0; ++it) {
        if (it > SPIN_LIMIT) SPIN_FAIL;
      }
      TS(24);
      mbar_expect_tx(bar_at, 20480);
      tma_load2d(sb + SM_AT, &tm_aT, T2 * 64, dq * 160, bar_at);
    }
  }
}

typedef CUresult (*EncodeFn)(CUtensorMap*, CUtensorMapDataType, cuuint32_t, void*, const cuuint64_t*, const cuuint64_t*,
                             const cuuint32_t*, const cuuint32_t*, CUtensorMapInterleave, CUtensorMapSwizzle,
                             CUtensorMapL2promotion, CUtensorMapFloatOOBfill);

static void make_map(EncodeFn fn, CUtensorMap* m, const void* ptr, uint64_t inner, uint64_t outer, uint32_t box_in, uint32_t box_out,
                     CUtensorMapSwizzle swz) {
  cuuint64_t dims[2] = {inner, outer};
  cuuint64_t strides[1] = {inner * 2};
  cuuint32_t box[2] = {box_in, box_out};
  cuuint32_t es[2] = {1, 1};
  CUresult r = fn(m, CU_TENSOR_MAP_DATA_TYPE_BFLOAT16, 2, const_cast<void*>(ptr), dims, strides, box, es, CU_TENSOR_MAP_INTERLEAVE_NONE, swz,
     CU_TENSOR_MAP_L2_PROMOTION_L2_256B, CU_TENSOR_MAP_FLOAT_OOB_FILL_NONE);
  (void)r;
}

static void make_map3(EncodeFn fn, CUtensorMap* m, const void* ptr, uint64_t d0, uint64_t d1, uint64_t d2, uint64_t s1, uint64_t s2,
                      uint32_t b0, uint32_t b1, uint32_t b2, CUtensorMapSwizzle swz) {
  cuuint64_t dims[3] = {d0, d1, d2};
  cuuint64_t strides[2] = {s1, s2};
  cuuint32_t box[3] = {b0, b1, b2};
  cuuint32_t es[3] = {1, 1, 1};
  CUresult r = fn(m, CU_TENSOR_MAP_DATA_TYPE_BFLOAT16, 3, const_cast<void*>(ptr), dims, strides, box, es, CU_TENSOR_MAP_INTERLEAVE_NONE, swz,
     CU_TENSOR_MAP_L2_PROMOTION_L2_256B, CU_TENSOR_MAP_FLOAT_OOB_FILL_NONE);
  (void)r;
}

extern "C" void kernel_launch(void* const* d_in, const int* in_sizes, int n_in, void* d_out, int out_size) {
  static EncodeFn fn = nullptr;
  static CUtensorMap tm_x, tm_w1, tm_slab, tm_ut, tm_hst, tm_hld, tm_w2, tm_aT, tm_ast, tm_out;
  static void *pg = nullptr, *pf = nullptr, *pep = nullptr, *pu = nullptr, *pw = nullptr;
  static const void *c_x = nullptr, *c_w1 = nullptr, *c_w2 = nullptr, *c_out = nullptr;
  if (!fn) {
    void* f = nullptr;
    cudaDriverEntryPointQueryResult qr;
    cudaGetDriverEntryPoint("cuTensorMapEncodeTiled", &f, cudaEnableDefault, &qr);
    fn = (EncodeFn)f;
    cudaFuncSetAttribute(fused_kernel, cudaFuncAttributeMaxDynamicSharedMemorySize, SMEM_BYTES);
    void *ph, *pa;
    cudaGetSymbolAddress(&ph, g_h);
    cudaGetSymbolAddress(&pa, g_aT);
    cudaGetSymbolAddress(&pu, g_uT);
    cudaGetSymbolAddress(&pw, g_w2p);
    cudaGetSymbolAddress(&pg, g_gate);
    cudaGetSymbolAddress(&pf, g_flag);
    cudaGetSymbolAddress(&pep, g_epoch);
    make_map(fn, &tm_hst, ph, 64, 24 * L_, 64, 16, CU_TENSOR_MAP_SWIZZLE_128B);
    make_map(fn, &tm_hld, ph, 64, 24 * L_, 64, 64, CU_TENSOR_MAP_SWIZZLE_128B);
    make_map(fn, &tm_aT, pa, L_, D_, 64, 160, CU_TENSOR_MAP_SWIZZLE_128B);
    make_map(fn, &tm_ast, pa, 64, 32 * D_, 64, 32, CU_TENSOR_MAP_SWIZZLE_128B);
    make_map3(fn, &tm_ut, pu, 592, D_, 4, 4736, 1184, 32, 80, 4, CU_TENSOR_MAP_SWIZZLE_64B);
  }
  if (c_x != d_in[0]) {
    make_map(fn, &tm_x, d_in[0], D_, L_, 64, 128, CU_TENSOR_MAP_SWIZZLE_128B);
    make_map(fn, &tm_slab, d_in[0], D_, L_, 80, 128, CU_TENSOR_MAP_SWIZZLE_NONE);
    c_x = d_in[0];
  }
  if (c_w1 != d_in[10]) { make_map3(fn, &tm_w1, d_in[10], 64, D_, 24, F_ * 2, 128, 64, 32, 3, CU_TENSOR_MAP_SWIZZLE_128B); c_w1 = d_in[10]; }
  if (c_w2 != d_in[12]) { make_map3(fn, &tm_w2, d_in[12], 32, F_, 20, D_ * 2, 64, 32, 16, 5, CU_TENSOR_MAP_SWIZZLE_64B); c_w2 = d_in[12]; }
  if (c_out != d_out) { make_map3(fn, &tm_out, d_out, 32, L_, 20, D_ * 2, 64, 32, 16, 5, CU_TENSOR_MAP_SWIZZLE_64B); c_out = d_out; }
  Params p;
  p.u = (const bf16*)d_in[0];
  p.Are = (const bf16*)d_in[1];
  p.Aim = (const bf16*)d_in[2];
  p.Bre = (const bf16*)d_in[3];
  p.Bim = (const bf16*)d_in[4];
  p.Cre = (const bf16*)d_in[5];
  p.Cim = (const bf16*)d_in[6];
  p.logdt = (const bf16*)d_in[7];
  p.Dsk = (const bf16*)d_in[8];
  p.w1 = (const bf16*)d_in[10];
  p.b1 = (const bf16*)d_in[11];
  p.w2 = (const bf16*)d_in[12];
  p.b2 = (const bf16*)d_in[13];
  p.gate_w = (const bf16*)d_in[14];
  p.uT = (const bf16*)pu;
  p.w2p = (bf16*)pw;
  p.gate = (unsigned*)pg;
  p.flag = (unsigned*)pf;
  p.epoch = (unsigned*)pep;
  fused_kernel<<<NCTA, 512, SMEM_BYTES, cudaStreamPerThread>>>(tm_x, tm_w1, tm_slab, tm_ut, tm_hst, tm_hld, tm_w2, tm_aT, tm_ast, tm_out, p);
}
```

```cpp
#include <cuda_runtime.h>
#include <cuda_bf16.h>
#include <cuda_fp16.h>
#include <cuda.h>
#include <stdint.h>
#include <string.h>

typedef __nv_bfloat16 bf16;
typedef __nv_bfloat162 bf162;

constexpr int L_ = 2048, D_ = 640, NM_ = 192, F_ = 1536;
constexpr int NCTA = 128;

__device__ bf16 g_h[L_ * F_];
__device__ bf16 g_aT[D_ * L_];
__device__ bf16 g_uT[D_ * L_];
__device__ bf16 g_w2p[F_ * D_];
__device__ unsigned g_gate[L_];
__device__ unsigned g_flag[(256 + 16) * 8];
__device__ unsigned g_epoch[NCTA];
__device__ unsigned g_err;
#define TS(i)
#define TR(i)

#define XE 1
#define EA 0
#define UKB 8
#define G1S 2
#define G2S 1
#define RPK 6
#define USTEP 5
#define KS
#define UW 2
#define SVW 3
#define TQ_TID 0
#define SPIN_LIMIT 2000000
#define SPIN_FAIL __trap()
__device__ __forceinline__ uint32_t smem_u32(const void* p) { return (uint32_t)__cvta_generic_to_shared(p); }
__device__ __forceinline__ void mbar_init(uint32_t bar, uint32_t cnt) {
  asm volatile("mbarrier.init.shared::cta.b64 [%0], %1;" ::"r"(bar), "r"(cnt) : "memory");
}
__device__ __forceinline__ void mbar_arrive(uint32_t bar) {
  asm volatile("mbarrier.arrive.shared::cta.b64 _, [%0];" ::"r"(bar) : "memory");
}
__device__ __forceinline__ void mbar_expect_tx(uint32_t bar, uint32_t bytes) {
  asm volatile("mbarrier.arrive.expect_tx.shared::cta.b64 _, [%0], %1;" ::"r"(bar), "r"(bytes) : "memory");
}
__device__ __forceinline__ bool mbar_try(uint32_t bar, uint32_t parity) {
  uint32_t ok;
  asm volatile("{.reg .pred p; mbarrier.test_wait.parity.shared::cta.b64 p, [%1], %2; selp.u32 %0,1,0,p;}"
               : "=r"(ok) : "r"(bar), "r"(parity) : "memory");
  return ok != 0;
}
__device__ __forceinline__ void mbar_wait(uint32_t bar, uint32_t parity) {
  asm volatile(
      "{\n.reg .pred p;\n.reg .u32 c;\nmov.u32 c, 0;\n"
      "WL:\nmbarrier.try_wait.parity.shared::cta.b64 p, [%0], %1;\n@p bra WD;\n"
      "add.u32 c, c, 1;\nsetp.lt.u32 p, c, 4000000;\n@p bra WL;\ntrap;\nWD:\n}"
      ::"r"(bar), "r"(parity) : "memory");
}
__device__ __forceinline__ bool mbar_wait2(uint32_t b0, uint32_t p0, uint32_t b1, uint32_t p1) {
  uint32_t ok;
  asm volatile(
      "{\n.reg .pred p;\n.reg .u32 c;\nmov.u32 c, 0;\nmov.u32 %0, 1;\n"
      "WL:\nmbarrier.test_wait.parity.shared::cta.b64 p, [%1], %2;\n@p bra WD;\n"
      "add.u32 c, c, 1;\nmbarrier.test_wait.parity.shared::cta.b64 p, [%3], %4;\nsetp.gt.or.u32 p, c, 4000000, p;\n@!p bra WL;\nmov.u32 %0, 0;\nWD:\n}"
      : "=r"(ok) : "r"(b0), "r"(p0), "r"(b1), "r"(p1) : "memory");
  return ok != 0;
}
__device__ __forceinline__ void tma_load2d(uint32_t dst, const CUtensorMap* tm, int c0, int c1, uint32_t bar) {
  asm volatile("cp.async.bulk.tensor.2d.shared::cluster.global.mbarrier::complete_tx::bytes [%0], [%1, {%3, %4}], [%2];"
               ::"r"(dst), "l"(tm), "r"(bar), "r"(c0), "r"(c1) : "memory");
}
__device__ __forceinline__ void tma_load3d_mc(uint32_t dst, const CUtensorMap* tm, int c0, int c1, int c2, uint32_t bar) {
  asm volatile("cp.async.bulk.tensor.3d.shared::cluster.global.mbarrier::complete_tx::bytes.multicast::cluster [%0], [%1, {%3, %4, %5}], [%2], %6;"
               ::"r"(dst), "l"(tm), "r"(bar), "r"(c0), "r"(c1), "r"(c2), "h"((uint16_t)3) : "memory");
}
__device__ __forceinline__ void tma_load3d(uint32_t dst, const CUtensorMap* tm, int c0, int c1, int c2, uint32_t bar) {
  asm volatile("cp.async.bulk.tensor.3d.shared::cluster.global.mbarrier::complete_tx::bytes [%0], [%1, {%3, %4, %5}], [%2];"
               ::"r"(dst), "l"(tm), "r"(bar), "r"(c0), "r"(c1), "r"(c2) : "memory");
}
__device__ __forceinline__ void tma_load4d(uint32_t dst, const CUtensorMap* tm, int c0, int c1, int c2, int c3, uint32_t bar) {
  asm volatile("cp.async.bulk.tensor.4d.shared::cluster.global.mbarrier::complete_tx::bytes [%0], [%1, {%3, %4, %5, %6}], [%2];"
               ::"r"(dst), "l"(tm), "r"(bar), "r"(c0), "r"(c1), "r"(c2), "r"(c3) : "memory");
}
__device__ __forceinline__ void tma_store3d(const CUtensorMap* tm, uint32_t src, int c0, int c1, int c2) {
  asm volatile("cp.async.bulk.tensor.3d.global.shared::cta.bulk_group [%0, {%2, %3, %4}], [%1];"
               ::"l"(tm), "r"(src), "r"(c0), "r"(c1), "r"(c2) : "memory");
}
__device__ __forceinline__ void tma_pf3d(const CUtensorMap* tm, int c0, int c1, int c2) {
  asm volatile("cp.async.bulk.prefetch.tensor.3d.L2.global [%0, {%1, %2, %3}];" ::"l"(tm), "r"(c0), "r"(c1), "r"(c2) : "memory");
}
__device__ __forceinline__ void l2_prefetch(const void* p, uint32_t bytes) {
  asm volatile("cp.async.bulk.prefetch.L2.global [%0], %1;" ::"l"(p), "r"(bytes) : "memory");
}
__device__ __forceinline__ void prefetch_tmap(const CUtensorMap* tm) { asm volatile("prefetch.tensormap [%0];" ::"l"(tm) : "memory"); }
__device__ __forceinline__ uint32_t mapa(uint32_t addr, uint32_t rank) {
  uint32_t r;
  asm("mapa.shared::cluster.u32 %0, %1, %2;" : "=r"(r) : "r"(addr), "r"(rank));
  return r;
}
__device__ __forceinline__ void mbar_arrive_cluster(uint32_t bar) {
  asm volatile("mbarrier.arrive.shared::cluster.b64 _, [%0];" ::"r"(bar) : "memory");
}
__device__ __forceinline__ void cluster_arrive() { asm volatile("barrier.cluster.arrive.relaxed.aligned;" ::: "memory"); }
__device__ __forceinline__ void cluster_wait() { asm volatile("barrier.cluster.wait.aligned;" ::: "memory"); }
__device__ __forceinline__ void stsm_x4_t(uint32_t addr, uint32_t a, uint32_t b, uint32_t c, uint32_t d) {
  asm volatile("stmatrix.sync.aligned.m8n8.x4.trans.shared.b16 [%0], {%1,%2,%3,%4};" ::"r"(addr), "r"(a), "r"(b), "r"(c), "r"(d) : "memory");
}
__device__ __forceinline__ void stsm_x4(uint32_t addr, uint32_t a, uint32_t b, uint32_t c, uint32_t d) {
  asm volatile("stmatrix.sync.aligned.m8n8.x4.shared.b16 [%0], {%1,%2,%3,%4};" ::"r"(addr), "r"(a), "r"(b), "r"(c), "r"(d) : "memory");
}
__device__ __forceinline__ void tma_store2d(const CUtensorMap* tm, uint32_t src, int c0, int c1) {
  asm volatile("cp.async.bulk.tensor.2d.global.shared::cta.bulk_group [%0, {%2, %3}], [%1];"
               ::"l"(tm), "r"(src), "r"(c0), "r"(c1) : "memory");
}
__device__ __forceinline__ void bulk_load(uint32_t dst, const void* src, uint32_t bytes, uint32_t bar) {
  asm volatile("cp.async.bulk.shared::cluster.global.mbarrier::complete_tx::bytes [%0], [%1], %2, [%3];" ::"r"(dst), "l"(src), "r"(bytes), "r"(bar) : "memory");
}
__device__ __forceinline__ void bulk_load_mc(uint32_t dst, const void* src, uint32_t bytes, uint32_t bar) {
  asm volatile("cp.async.bulk.shared::cluster.global.mbarrier::complete_tx::bytes.multicast::cluster [%0], [%1], %2, [%3], %4;"
               ::"r"(dst), "l"(src), "r"(bytes), "r"(bar), "h"((uint16_t)3) : "memory");
}
__device__ __forceinline__ void bulk_store(void* dst, uint32_t src, uint32_t bytes) {
  asm volatile("cp.async.bulk.global.shared::cta.bulk_group [%0], [%1], %2;" ::"l"(dst), "r"(src), "r"(bytes) : "memory");
}
__device__ __forceinline__ void bulk_commit() { asm volatile("cp.async.bulk.commit_group;" ::: "memory"); }
__device__ __forceinline__ void bulk_wait_read0() { asm volatile("cp.async.bulk.wait_group.read 0;" ::: "memory"); }
template <int N> __device__ __forceinline__ void bulk_wait() { asm volatile("cp.async.bulk.wait_group %0;" ::"n"(N) : "memory"); }
__device__ __forceinline__ void fence_async_smem() { asm volatile("fence.proxy.async.shared::cta;" ::: "memory"); }
__device__ __forceinline__ void named_bar(int id, int n) { asm volatile("bar.sync %0, %1;" ::"r"(id), "r"(n) : "memory"); }
__device__ __forceinline__ void named_arrive(int id, int n) { asm volatile("bar.arrive %0, %1;" ::"r"(id), "r"(n) : "memory"); }
__device__ __forceinline__ void wg_fence() { asm volatile("wgmma.fence.sync.aligned;" ::: "memory"); }
__device__ __forceinline__ void wg_commit() { asm volatile("wgmma.commit_group.sync.aligned;" ::: "memory"); }
template <int N> __device__ __forceinline__ void wg_wait() { asm volatile("wgmma.wait_group.sync.aligned %0;" ::"n"(N) : "memory"); }
__device__ __forceinline__ uint64_t make_desc(uint32_t addr, uint32_t lbo, uint32_t sbo, uint32_t swz) {
  return (uint64_t)((addr & 0x3FFFF) >> 4) | ((uint64_t)(lbo >> 4) << 16) | ((uint64_t)(sbo >> 4) << 32) | ((uint64_t)swz << 62);
}
__device__ __forceinline__ void red_relaxed_add(unsigned* p, unsigned v) {
  asm volatile("red.relaxed.gpu.global.add.u32 [%0], %1;" ::"l"(p), "r"(v) : "memory");
}
__device__ __forceinline__ unsigned ld_relaxed(const unsigned* p) {
  unsigned v;
  asm volatile("ld.relaxed.gpu.global.u32 %0, [%1];" : "=r"(v) : "l"(p) : "memory");
  return v;
}
__device__ __forceinline__ void spin_ge(const unsigned* p, unsigned need, unsigned v) {
  asm volatile(
      "{\n.reg .pred p;\n.reg .u32 c, v;\nmov.u32 c, 0;\nmov.u32 v, %2;\n"
      "SL:\nsub.u32 v, v, %1;\nsetp.ge.s32 p, v, 0;\n@p bra SD;\nld.relaxed.gpu.global.u32 v, [%0];\n"
      "add.u32 c, c, 1;\nsetp.lt.u32 p, c, 2000000;\n@p bra SL;\ntrap;\nSD:\n}"
      ::"l"(p), "r"(need), "r"(v) : "memory");
}
__device__ __forceinline__ void st_relaxed(unsigned* p, unsigned v) {
  asm volatile("st.relaxed.gpu.global.u32 [%0], %1;" ::"l"(p), "r"(v) : "memory");
}
__device__ __forceinline__ uint32_t pack_bf16(float lo, float hi) {
  uint32_t r;
  asm("cvt.rn.bf16x2.f32 %0, %1, %2;" : "=r"(r) : "f"(hi), "f"(lo));
  return r;
}
__device__ __forceinline__ uint32_t as_u32(bf162 v) { return *reinterpret_cast<uint32_t*>(&v); }
__device__ __forceinline__ bf162 as_bf162(uint32_t v) { return *reinterpret_cast<bf162*>(&v); }

#define R4(d, b) "+f"(d[b + 0]), "+f"(d[b + 1]), "+f"(d[b + 2]), "+f"(d[b + 3])
#define R8(d, b) R4(d, b), R4(d, b + 4)
__device__ __forceinline__ void wgmma_n192(float* d, uint64_t da, uint64_t db) {
  asm volatile("wgmma.mma_async.sync.aligned.m64n192k16.f32.bf16.bf16 {%0,%1,%2,%3,%4,%5,%6,%7,%8,%9,%10,%11,%12,%13,%14,%15,%16,%17,%18,%19,%20,%21,%22,%23,%24,%25,%26,%27,%28,%29,%30,%31,%32,%33,%34,%35,%36,%37,%38,%39,%40,%41,%42,%43,%44,%45,%46,%47,%48,%49,%50,%51,%52,%53,%54,%55,%56,%57,%58,%59,%60,%61,%62,%63,%64,%65,%66,%67,%68,%69,%70,%71,%72,%73,%74,%75,%76,%77,%78,%79,%80,%81,%82,%83,%84,%85,%86,%87,%88,%89,%90,%91,%92,%93,%94,%95}, %96, %97, 1, 1, 1, 0, 1;"
      : R8(d, 0), R8(d, 8), R8(d, 16), R8(d, 24), R8(d, 32), R8(d, 40), R8(d, 48), R8(d, 56), R8(d, 64), R8(d, 72), R8(d, 80), R8(d, 88)
      : "l"(da), "l"(db));
}
__device__ __forceinline__ void wgmma_n160(float* d, uint64_t da, uint64_t db, uint32_t sd) {
  asm volatile("{.reg .pred p; setp.ne.u32 p, %82, 0;\nwgmma.mma_async.sync.aligned.m64n160k16.f32.bf16.bf16 {%0,%1,%2,%3,%4,%5,%6,%7,%8,%9,%10,%11,%12,%13,%14,%15,%16,%17,%18,%19,%20,%21,%22,%23,%24,%25,%26,%27,%28,%29,%30,%31,%32,%33,%34,%35,%36,%37,%38,%39,%40,%41,%42,%43,%44,%45,%46,%47,%48,%49,%50,%51,%52,%53,%54,%55,%56,%57,%58,%59,%60,%61,%62,%63,%64,%65,%66,%67,%68,%69,%70,%71,%72,%73,%74,%75,%76,%77,%78,%79}, %80, %81, p, 1, 1, 0, 1;}"
      : R8(d, 0), R8(d, 8), R8(d, 16), R8(d, 24), R8(d, 32), R8(d, 40), R8(d, 48), R8(d, 56), R8(d, 64), R8(d, 72)
      : "l"(da), "l"(db), "r"(sd));
}
__device__ __forceinline__ void wgmma_n48_tt(float* d, uint64_t da, uint64_t db, uint32_t sd) {
  asm volatile(
      "{.reg .pred p; setp.ne.u32 p, %26, 0;\n"
      "wgmma.mma_async.sync.aligned.m64n48k16.f32.f16.f16 "
      "{%0,%1,%2,%3,%4,%5,%6,%7,%8,%9,%10,%11,%12,%13,%14,%15,%16,%17,%18,%19,%20,%21,%22,%23}, %24, %25, p, 1, 1, 1, 1;}"
      : R8(d, 0), R8(d, 8), R8(d, 16)
      : "l"(da), "l"(db), "r"(sd));
}
template <int SD, int TB> __device__ __forceinline__ void wgr32(float* d, uint32_t a0, uint32_t a1, uint32_t a2, uint32_t a3, uint64_t db) {
  asm volatile(
      "wgmma.mma_async.sync.aligned.m64n32k16.f32.bf16.bf16 "
      "{%0,%1,%2,%3,%4,%5,%6,%7,%8,%9,%10,%11,%12,%13,%14,%15}, {%16,%17,%18,%19}, %20, %21, 1, 1, %22;"
      : R8(d, 0), R8(d, 8) : "r"(a0), "r"(a1), "r"(a2), "r"(a3), "l"(db), "n"(SD), "n"(TB));
}
template <int SD, int TB> __device__ __forceinline__ void wgr48(float* d, uint32_t a0, uint32_t a1, uint32_t a2, uint32_t a3, uint64_t db) {
  asm volatile(
      "wgmma.mma_async.sync.aligned.m64n48k16.f32.bf16.bf16 "
      "{%0,%1,%2,%3,%4,%5,%6,%7,%8,%9,%10,%11,%12,%13,%14,%15,%16,%17,%18,%19,%20,%21,%22,%23}, {%24,%25,%26,%27}, %28, %29, 1, 1, %30;"
      : R8(d, 0), R8(d, 8), R8(d, 16) : "r"(a0), "r"(a1), "r"(a2), "r"(a3), "l"(db), "n"(SD), "n"(TB));
}
template <int SD> __device__ __forceinline__ void wgs48(float* d, uint64_t da, uint64_t db) {
  asm volatile(
      "wgmma.mma_async.sync.aligned.m64n48k16.f32.bf16.bf16 "
      "{%0,%1,%2,%3,%4,%5,%6,%7,%8,%9,%10,%11,%12,%13,%14,%15,%16,%17,%18,%19,%20,%21,%22,%23}, %24, %25, %26, 1, 1, 0, 0;"
      : R8(d, 0), R8(d, 8), R8(d, 16) : "l"(da), "l"(db), "n"(SD));
}
template <int SD> __device__ __forceinline__ void wgs32(float* d, uint64_t da, uint64_t db) {
  asm volatile(
      "wgmma.mma_async.sync.aligned.m64n32k16.f32.bf16.bf16 "
      "{%0,%1,%2,%3,%4,%5,%6,%7,%8,%9,%10,%11,%12,%13,%14,%15}, %16, %17, %18, 1, 1, 0, 0;"
      : R8(d, 0), R8(d, 8) : "l"(da), "l"(db), "n"(SD));
}
__device__ __forceinline__ void wgs64(float* d, uint64_t da, uint64_t db) {
  asm volatile(
      "wgmma.mma_async.sync.aligned.m64n64k16.f32.bf16.bf16 "
      "{%0,%1,%2,%3,%4,%5,%6,%7,%8,%9,%10,%11,%12,%13,%14,%15,%16,%17,%18,%19,%20,%21,%22,%23,%24,%25,%26,%27,%28,%29,%30,%31}, %32, %33, 1, 1, 1, 0, 0;"
      : R8(d, 0), R8(d, 8), R8(d, 16), R8(d, 24) : "l"(da), "l"(db));
}
#define U4(d, b) "=r"(d[b + 0]), "=r"(d[b + 1]), "=r"(d[b + 2]), "=r"(d[b + 3])
__device__ __forceinline__ void wgs64h(uint32_t* d, uint64_t da, uint64_t db) {
  asm volatile(
      "wgmma.mma_async.sync.aligned.m64n64k16.f16.f16.f16 "
      "{%0,%1,%2,%3,%4,%5,%6,%7,%8,%9,%10,%11,%12,%13,%14,%15}, %16, %17, 0, 1, 1, 0, 0;"
      : U4(d, 0), U4(d, 4), U4(d, 8), U4(d, 12) : "l"(da), "l"(db));
}
__device__ __forceinline__ void stsm_x2_t(uint32_t addr, uint32_t a, uint32_t b) {
  asm volatile("stmatrix.sync.aligned.m8n8.x2.trans.shared.b16 [%0], {%1,%2};" ::"r"(addr), "r"(a), "r"(b) : "memory");
}
__device__ __forceinline__ uint32_t lds32(uint32_t a) { uint32_t v; asm volatile("ld.shared.u32 %0, [%1];" : "=r"(v) : "r"(a)); return v; }
__device__ __forceinline__ float lds32f(uint32_t a) { float v; asm volatile("ld.shared.f32 %0, [%1];" : "=f"(v) : "r"(a)); return v; }
__device__ __forceinline__ uint32_t lds16(uint32_t a) { uint16_t v; asm volatile("ld.shared.u16 %0, [%1];" : "=h"(v) : "r"(a)); return v; }
__device__ __forceinline__ float4 lds128f(uint32_t a) { float4 v; asm volatile("ld.shared.v4.f32 {%0,%1,%2,%3}, [%4];" : "=f"(v.x), "=f"(v.y), "=f"(v.z), "=f"(v.w) : "r"(a)); return v; }
__device__ __forceinline__ uint2 lds64u(uint32_t a) { uint2 v; asm volatile("ld.shared.v2.u32 {%0,%1}, [%2];" : "=r"(v.x), "=r"(v.y) : "r"(a)); return v; }
__device__ __forceinline__ uint4 lds128u(uint32_t a) { uint4 v; asm volatile("ld.shared.v4.u32 {%0,%1,%2,%3}, [%4];" : "=r"(v.x), "=r"(v.y), "=r"(v.z), "=r"(v.w) : "r"(a)); return v; }
__device__ __forceinline__ void sts16(uint32_t a, uint32_t v) { asm volatile("st.shared.u16 [%0], %1;" ::"r"(a), "h"((uint16_t)v) : "memory"); }
__device__ __forceinline__ void sts32(uint32_t a, uint32_t v) { asm volatile("st.shared.u32 [%0], %1;" ::"r"(a), "r"(v) : "memory"); }
__device__ __forceinline__ void sts64f(uint32_t a, float x, float y) { asm volatile("st.shared.v2.f32 [%0], {%1,%2};" ::"r"(a), "f"(x), "f"(y) : "memory"); }
__device__ __forceinline__ void sts128f(uint32_t a, float x, float y, float z, float w) { asm volatile("st.shared.v4.f32 [%0], {%1,%2,%3,%4};" ::"r"(a), "f"(x), "f"(y), "f"(z), "f"(w) : "memory"); }
__device__ __forceinline__ void sts128u(uint32_t a, uint32_t x, uint32_t y, uint32_t z, uint32_t w) { asm volatile("st.shared.v4.u32 [%0], {%1,%2,%3,%4};" ::"r"(a), "r"(x), "r"(y), "r"(z), "r"(w) : "memory"); }
__device__ __forceinline__ void ldsm4(uint32_t addr, uint32_t* r) {
  asm volatile("ldmatrix.sync.aligned.m8n8.x4.shared.b16 {%0,%1,%2,%3}, [%4];" : "=r"(r[0]), "=r"(r[1]), "=r"(r[2]), "=r"(r[3]) : "r"(addr));
}
__device__ __forceinline__ void ldsm4t(uint32_t addr, uint32_t* r) {
  asm volatile("ldmatrix.sync.aligned.m8n8.x4.trans.shared.b16 {%0,%1,%2,%3}, [%4];" : "=r"(r[0]), "=r"(r[1]), "=r"(r[2]), "=r"(r[3]) : "r"(addr));
}
__device__ __forceinline__ float bf_lo(uint32_t v) { return __uint_as_float(v << 16); }
__device__ __forceinline__ float bf_hi(uint32_t v) { return __uint_as_float(v & 0xffff0000u); }
__device__ __forceinline__ uint32_t ldg16(const bf16* p) {
  uint32_t v;
  asm volatile("ld.global.nc.u16 %0, [%1];" : "=r"(v) : "l"(p));
  return v;
}
__device__ __forceinline__ float2 cmul(float2 a, float2 b) { return make_float2(fmaf(a.x, b.x, -a.y * b.y), fmaf(a.x, b.y, a.y * b.x)); }
__device__ __forceinline__ float2 csqr(float2 a) { return make_float2(fmaf(a.x, a.x, -a.y * a.y), (a.x + a.x) * a.y); }
__device__ __forceinline__ float2 cexp2(float ar2, float ai) {
  float m;
  asm("ex2.approx.ftz.f32 %0, %1;" : "=f"(m) : "f"(ar2));
  const float k = fmaf(ai, 0.15915494f, 12582912.f) - 12582912.f;
  const float ph = fmaf(k, 1.7484555e-7f, fmaf(k, -6.2831855f, ai));
  return make_float2(m * __cosf(ph), m * __sinf(ph));
}
struct HC { __half2 re, im; };
__device__ __forceinline__ HC hmul(HC x, __half2 f) {
  const __half2 fr = __low2half2(f), fi = __high2half2(f);
  HC r;
  r.re = __hfma2(x.re, fr, __hmul2(__hneg2(x.im), fi));
  r.im = __hfma2(x.re, fi, __hmul2(x.im, fr));
  return r;
}
__device__ __forceinline__ HC hmulc(HC x, __half2 f) {
  const __half2 fr = __low2half2(f), fi = __high2half2(f);
  HC r;
  r.re = __hfma2(x.re, fr, __hmul2(x.im, fi));
  r.im = __hfma2(__hneg2(x.re), fi, __hmul2(x.im, fr));
  return r;
}
__device__ __forceinline__ uint32_t h_u32(__half2 v) { return *reinterpret_cast<uint32_t*>(&v); }
__device__ __forceinline__ void st_hc4(uint32_t a, const HC* v) {
  sts128u(a, h_u32(v[0].re), h_u32(v[1].re), h_u32(v[2].re), h_u32(v[3].re));
  sts128u(a + 128, h_u32(v[0].im), h_u32(v[1].im), h_u32(v[2].im), h_u32(v[3].im));
}
__device__ __forceinline__ uint32_t maxabs2(uint32_t a, uint32_t b) {
  uint32_t r;
  asm("max.xorsign.abs.bf16x2 %0, %1, %2;" : "=r"(r) : "r"(a), "r"(b));
  return r;
}
__device__ __forceinline__ float2 lds64f(uint32_t a) { float2 v; asm volatile("ld.shared.v2.f32 {%0,%1}, [%2];" : "=f"(v.x), "=f"(v.y) : "r"(a)); return v; }

constexpr int G1_STAGES = 3, G1_TX = 40960;
constexpr int SM_SLAB = 81920;
__host__ __device__ constexpr int x_off(int so) { return so == 0 ? 102400 : so == 1 ? 24576 : 65536; }
__host__ __device__ constexpr int w1_off(int so) { return so == 0 ? 118784 : so == 1 ? 0 : 40960; }
constexpr int G2_TX = 28672, SM_W2 = 8192;
constexpr int SM_KT = 143360, KT_BYTES = 2304, KT_S2 = 1152 + 128, KT_S3 = KT_S2 + 384;
constexpr int SM_WK = SM_KT + 5 * KT_BYTES;
constexpr int U0_PL = 1216, U0_BYTES = 4 * U0_PL;
constexpr int WS_X2 = 13568, WS_X3 = WS_X2 + 6144, WS_BYTES = 23936;
constexpr int SM_WS3 = SM_WK, SM_U0 = SM_WS3 + WS_BYTES, SM_WS2 = SM_U0 + 5 * U0_BYTES;
constexpr int SM_WINA = SM_WS2 + WS_BYTES, SM_SEL = SM_WINA + 2560;
constexpr int KG_BYTES = 28672, KG_B = 16384;
constexpr int SM_KG3 = SM_WK, SM_KG2 = SM_WINA - KG_BYTES;
constexpr int SM_AT = SM_W2 + 4 * G2_TX, SM_OUT = SM_W2;
constexpr int SM_MISC = SM_SEL + 384;
static_assert(KG_BYTES <= WS_BYTES + U0_BYTES && WS_X3 + 4128 <= WS_BYTES && 94 * 144 <= WS_X2 && SM_MISC % 128 == 0 && SM_U0 % 128 == 0, "smem");
static_assert(5 * G2_TX <= SM_KT && KT_S3 + 256 <= 2048, "smem");
constexpr int SM_B1 = SM_MISC + 256;
constexpr int SM_B2 = SM_B1 + 384;
constexpr int SM_G = SM_B2 + 320;
constexpr int SM_DSK = SM_G + 256;
constexpr int SM_DUMP = SM_DSK + 32;
constexpr int SM_TR = SM_MISC + 1408;
constexpr int SMEM_BYTES = SM_MISC + 2432;
constexpr uint32_t SB0 = 1024;
static_assert(SMEM_BYTES <= 232448, "smem");

struct Params {
  const bf16 *u, *Are, *Aim, *Bre, *Bim, *Cre, *Cim, *logdt, *Dsk, *w1, *b1, *w2, *b2, *gate_w;
  bf16 *aT, *w2p;
  unsigned *gate, *flag, *epoch;
};

#define TQ(k)
__device__ __forceinline__ uint32_t win_addr(int x, int odd, int hh) {
  const int j = odd ? (x + 2 - hh) >> 1 : x + 1;
  return (odd ? WS_X3 + (j >> 5) * 2048 + ((x ^ hh) & 1) * 1024 : WS_X2 + (j >> 5) * 1024) + (j & 3) * 256 + ((j >> 2) & 7) * 32 + 16 - 16 * hh;
}
__device__ __forceinline__ constexpr int u_off(int s) { return ((2 * s + 2) & 3) * (U0_PL >> 4) + ((2 * s + 14) >> 2); }

template <class H>
__device__ __forceinline__ void conv(uint32_t sb, uint32_t ws, uint32_t u0, uint32_t kt, int barid, uint32_t dsk2, int w4, int lane, uint32_t tq, H hook) {
  const int g = lane >> 2, c = lane & 3, hh = (lane >> 3) & 1;
  const uint64_t du = make_desc(SB0 + u0, U0_PL, 128, 0);
  const uint32_t ta = sb + kt + (8 * w4 + g - 4 * c) * 4;
  uint64_t dy = make_desc(SB0 + ws, 288, 144, 0), d2 = make_desc(SB0 + ws + WS_X2, 128, 1024, 0);
  asm volatile("" : "+l"(dy), "+l"(d2));
  float a3[16], a2[24], b2[16], a1[16];
  {
    float wa[24], wb[24];
    uint32_t e1[16], e2[16], F[16];
    const uint64_t dw = make_desc(SB0 + SM_WINA, 512, 128, 0), ds = make_desc(SB0 + SM_SEL, 128, 16, 0), dk = make_desc(SB0 + kt, 32, 128, 0);
    wg_fence();
    wgs64h(e1, dk, ds);
    wgs64h(e2, dk + 64, ds);
    wg_commit();
    wgs48<0>(wa, dw, du + u_off(17));
    wgs48<1>(wa, dw + 64, du + u_off(18));
    wg_commit();
    wgs48<0>(wb, dw, du + u_off(16));
    wgs48<1>(wb, dw + 64, du + u_off(17));
    wg_commit();
    hook();
    TQ(0);
    wg_wait<2>();
    TQ(9);
    {
      const int j = 16 * w4 + (lane & 15);
      const uint32_t ya = sb + ws + (86 - (j & ~1) + (j & 1)) * 144 + 112 - (lane & 16);
#pragma unroll
      for (int i = 0; i < 4; i++) stsm_x4(ya - 32 * i, e1[4 * i], e1[4 * i + 1], e1[4 * i + 2], e1[4 * i + 3]);
      if (w4 == 0) {
        const int r = lane & 7;
        const uint32_t yb = sb + (r == 0 || r > 4 ? SM_DUMP : ws + ((r & 1) ? 24 - r : 12 - r) * 144) + 112 - (lane >> 3) * 16;
        stsm_x4(yb, e2[0], e2[2], e2[4], e2[6]);
        stsm_x4(yb - 64, e2[8], e2[10], e2[12], e2[14]);
        if (lane == 0) sts128u(sb + ws + WS_X3 + 16, 0, 0, 0, 0);
      }
    }
#pragma unroll
    for (int i = 0; i < 16; i++) F[i] = lds32(ta + KT_S3 + 4 * (32 * (i & 1) - 16 * ((i >> 1) & 1) - (i >> 2)));
    const int x = 4 * ((lane >> 4) * 8 + (lane & 7)) - (w4 >> 1);
    const uint32_t xa = sb + ws + win_addr(x + 2, w4 & 1, hh), xb = sb + ws + win_addr(x, w4 & 1, hh);
    TQ(10);
    wg_wait<1>();
    TQ(11);
#pragma unroll
    for (int i = 0; i < 3; i++)
      if (i < 2 || !(w4 & 1))
        stsm_x4_t(xa + 2048 * i, pack_bf16(wa[8 * i], wa[8 * i + 1]), pack_bf16(wa[8 * i + 2], wa[8 * i + 3]),
                  pack_bf16(wa[8 * i + 4], wa[8 * i + 5]), pack_bf16(wa[8 * i + 6], wa[8 * i + 7]));
    wg_wait<0>();
#pragma unroll
    for (int i = 0; i < 3; i++)
      if (i < 2 || !(w4 & 1))
        stsm_x4_t(xb + 2048 * i, pack_bf16(wb[8 * i], wb[8 * i + 1]), pack_bf16(wb[8 * i + 2], wb[8 * i + 3]),
                  pack_bf16(wb[8 * i + 4], wb[8 * i + 5]), pack_bf16(wb[8 * i + 6], wb[8 * i + 7]));
    TQ(12);
    fence_async_smem();
    TQ(1);
    named_bar(barid, 128);
    const uint64_t d3 = d2 + ((WS_X3 - WS_X2) >> 4);
    wg_fence();
    wgr32<0, 1>(a3, F[0], F[1], F[2], F[3], d3);
    wgr32<1, 1>(a3, F[4], F[5], F[6], F[7], d3 + 16);
    wgr32<1, 1>(a3, F[8], F[9], F[10], F[11], d3 + 32);
    wgr32<1, 1>(a3, F[12], F[13], F[14], F[15], d3 + 48);
    wg_commit();
  }
  TQ(2);
  {
    uint32_t F[16], G[16];
#pragma unroll
    for (int i = 0; i < 16; i++) F[i] = lds32(ta + KT_S2 + 4 * (32 * (i & 1) - 16 * ((i >> 1) & 1) - (i >> 2)));
    wg_fence();
    wgr48<0, 1>(a2, F[0], F[1], F[2], F[3], d2);
#pragma unroll
    for (int s = 1; s < 4; s++) wgr48<1, 1>(a2, F[4 * s], F[4 * s + 1], F[4 * s + 2], F[4 * s + 3], d2 + 16 * s);
    wg_commit();
    wg_wait<1>();
#pragma unroll
    for (int i = 0; i < 16; i++) {
      if (i & 1) asm volatile("" : "=r"(G[i]));
      else G[i] = lds32(ta + KT_S2 + 4 * (64 - 16 * ((i >> 1) & 1) - (i >> 2)));
    }
    wg_fence();
    wgr32<0, 1>(b2, G[0], G[1], G[2], G[3], d2);
#pragma unroll
    for (int s = 1; s < 4; s++) wgr32<1, 1>(b2, G[4 * s], G[4 * s + 1], G[4 * s + 2], G[4 * s + 3], d2 + 16 * s);
    wg_commit();
  }
  TQ(3);
  wg_wait<0>();
  wg_fence();
  wgs32<0>(a1, dy, du + u_off(16));
  wgs32<1>(a1, dy + 36, du + u_off(17));
  wgs32<1>(a1, dy + 72, du + u_off(18));
  wg_commit();
  named_bar(barid, 128);
  TQ(4);
  {
    const int o = 8 * w4 + g;
    const uint32_t p3 = sb + ws + WS_X3 + ((16 * o + 2 * c) ^ (((o >> 2) & 3) << 3)) * 4, p2 = sb + ws + WS_X2 + ((8 * o + 2 * c) ^ (w4 << 3)) * 4;
#pragma unroll
    for (int hf = 0; hf < 2; hf++) {
      sts64f(p3 ^ (hf * 32), a3[4 * hf], a3[4 * hf + 1]);
      sts64f((p3 ^ (hf * 32)) + 2048, a3[8 + 4 * hf] + a3[4 * hf + 2], a3[8 + 4 * hf + 1] + a3[4 * hf + 3]);
    }
#pragma unroll
    for (int b = 0; b < 6; b++) {
      float x = a2[4 * b], y = a2[4 * b + 1];
      if (b >= 1) { x += a2[4 * b - 2]; y += a2[4 * b - 1]; }
      if (b >= 2) { x += b2[4 * b - 8]; y += b2[4 * b - 7]; }
      sts64f(p2 + b * 1024, x, y);
    }
  }
  TQ(5);
  wg_wait<0>();
  named_bar(barid, 128);
  TQ(6);
  float acc[32];
  {
    const uint32_t pa = sb + ws + WS_X2 + (((24 - 8 * w4 + g) ^ (c << 3)) + 64 * c) * 4;
#pragma unroll
    for (int j = 0; j < 8; j++) {
      acc[4 * j] = j < 2 ? 0.f : lds32f(pa + (j - 2) * 1024);
      acc[4 * j + 1] = j < 2 ? 0.f : lds32f(pa + (j - 2) * 1024 + 128);
      if (j >= 4) { acc[4 * j] += a1[4 * j - 16]; acc[4 * j + 1] += a1[4 * j - 15]; }
      acc[4 * j + 2] = j < 3 || j == 7 ? 0.f : lds32f(pa + 6144 + (j - 3) * 1024);
      acc[4 * j + 3] = j < 3 || j == 7 ? 0.f : lds32f(pa + 6144 + (j - 3) * 1024 + 128);
    }
    asm volatile("" : R8(acc, 0), R8(acc, 8), R8(acc, 16), R8(acc, 24));
    wg_fence();
#pragma unroll
    for (int s = 0; s < 19; s++) wgs64(acc, dy + 36 * (s + 3), du + u_off(s));
    wg_commit();
  }
  TQ(7);
  uint32_t uu[8];
  const uint32_t ua = sb + u0 + 192 + (3 - w4) * U0_PL + lane * 16;
  ldsm4t(ua, uu);
  ldsm4t(ua + 512, uu + 4);
#pragma unroll
  for (int j = 0; j < 8; j++) uu[j] = as_u32(__hmul2_rn(as_bf162(uu[j]), as_bf162(dsk2)));
  wg_wait<0>();
  named_bar(barid, 128);
  TQ(8);
#pragma unroll
  for (int j = 0; j < 8; j++) {
    float x = acc[4 * j], y = acc[4 * j + 1];
    if (j) { x += acc[4 * j - 2]; y += acc[4 * j - 1]; }
    uu[j] = as_u32(__hadd2_rn(as_bf162(pack_bf16(x, y)), as_bf162(uu[j])));
  }
  const uint32_t oa = sb + u0 + (lane >> 1) * 128 + (((4 * (lane & 1) + 3 - w4) ^ ((lane >> 1) & 7)) << 4);
  stsm_x4_t(oa, uu[0], uu[1], uu[2], uu[3]);
  stsm_x4_t(oa + 2048, uu[4], uu[5], uu[6], uu[7]);
  TQ(13);
}

__device__ __forceinline__ void bc_scale(uint32_t kt, int lane, float dt, float& cs, float& sc) {
  uint32_t mx[2];
#pragma unroll
  for (int i = 0; i < 2; i++) {
    const uint2 a = lds64u(kt + 768 + 768 * i + lane * 8), b = lds64u(kt + 1024 + 768 * i + lane * 8), d = lds64u(kt + 1280 + 768 * i + lane * 8);
    const uint32_t m = maxabs2(maxabs2(maxabs2(a.x, a.y), maxabs2(b.x, b.y)), maxabs2(d.x, d.y));
    mx[i] = min(max(__reduce_max_sync(0xffffffffu, max((m << 16) & 0x7f800000u, m & 0x7f800000u)), 64u << 23), 190u << 23);
  }
  cs = __uint_as_float((254u << 23) - mx[0]) * __uint_as_float((254u << 23) - mx[1]);
  sc = dt * __uint_as_float(mx[0]) * __uint_as_float(mx[1]);
}
__device__ __forceinline__ void kt_store(uint32_t kt, uint32_t dump, int wh, int lane, const float* kv, float scale, int d) {
  const int g = lane >> 2, c = lane & 3;
  uint32_t v[6];
#pragma unroll
  for (int i = 0; i < 6; i++) v[i] = pack_bf16(kv[2 * i] * scale, kv[2 * i + 1] * scale);
  stsm_x4(kt + 32 + (16 * wh + (lane & 15)) * 32 + (lane & 16), v[0], v[1], v[2], v[3]);
  stsm_x2_t((lane & 4) ? kt + KT_S3 + (lane & 3) * 64 + wh * 32 + (lane & 8) * 2 : dump, v[4], v[5]);
  if (c < 2) {
    const uint32_t a = kt + KT_S2 + (32 * c + 16 * wh + g) * 4;
    sts32(a, v[4]);
    sts32(a + 32, v[5]);
  }
  if (wh && g == 7) {
    sts32(kt + 16 + c * 4, v[1]);
    if (c == 3) sts128u(kt + 67 * 16, v[3] >> 16, v[3] >> 16, v[3] >> 16, 0);
    if (c == 1) sts128u(kt + 68 * 16, v[5] & 0xffff0000u, 0, 0, v[5] >> 16);
  }
}

__global__ void __cluster_dims__(2, 1, 1) __launch_bounds__(512, 1)
fused_kernel(const __grid_constant__ CUtensorMap tm_x, const __grid_constant__ CUtensorMap tm_w1,
             const __grid_constant__ CUtensorMap tm_ut,
             const __grid_constant__ CUtensorMap tm_hst, const __grid_constant__ CUtensorMap tm_hld,
             const __grid_constant__ CUtensorMap tm_w2, const __grid_constant__ CUtensorMap tm_aT,
             const __grid_constant__ CUtensorMap tm_u0, const __grid_constant__ CUtensorMap tm_out, const Params p) {
  extern __shared__ __align__(1024) uint8_t smem_raw[];
  const uint32_t sraw = smem_u32(smem_raw);
  const uint32_t sb = sraw;
  if ((sb & 0xffffff) != SB0) __trap();
  const int tid = threadIdx.x, warp = __shfl_sync(0xffffffffu, tid >> 5, 0), lane = tid & 31;
  const int cta = blockIdx.x, cl = cta >> 1, rk = cta & 1;
  const int idx = (cl & 7) * 8 + (cl >> 3);
  const int sl = (idx & 3) + ((idx >> 3) & 1) * 4, tt = 2 * (((idx >> 2) & 1) + (idx >> 4) * 2) + rk;
  const int dq = idx & 3, T2 = 2 * tt + (sl >> 2);
  const uint32_t bar_full1 = sb + SM_MISC;
  const uint32_t bar_empty1 = bar_full1 + 24;
  const uint32_t bar_emptyx = bar_empty1 + 24;
  const uint32_t bar_full2 = bar_emptyx + 24;
  const uint32_t bar_empty2 = bar_full2 + 40;
  const uint32_t bar_ring = bar_empty2 + 40;
  const uint32_t bar_at = bar_ring + 8;
  const uint32_t bar_sf = bar_at + 8;
  const uint32_t bar_par = bar_sf + 8;
  const uint32_t bar_slab = bar_par + 8;
  const uint32_t bar_u = bar_slab + 8;
  const uint32_t bar_k4 = bar_u + 8;
  const uint32_t bar_fin = bar_k4 + 16;
  const uint32_t bar_rp = bar_fin + 8;
  const int k0 = (5 * sl) >> 2, ksw = (sl >> 1) & 1;
  auto kcol = [&](int kb) { return (kb < 2 ? k0 + (kb ^ ksw) : k0 + kb >= 10 ? k0 + kb - 10 : k0 + kb) * 64; };
  const uint32_t peer_off = mapa(sb, rk ^ 1) - sb;

  if (tid == 128) {
    for (int i = 1; i < G1_STAGES; i++) mbar_init(bar_full1 + 8 * i, 1);
    asm volatile("fence.mbarrier_init.release.cluster;" ::: "memory");
#pragma unroll
    for (int kb = 1; kb < G1_STAGES; kb++) {
      mbar_expect_tx(bar_full1 + 8 * kb, G1_TX);
      tma_load2d(sb + x_off(kb), &tm_x, kcol(kb), tt * 128, bar_full1 + 8 * kb);
    }
  }
  if (tid == 32) {
    for (int i = 0; i < (XE ? 1 : G1_STAGES); i++) mbar_init(bar_full1 + 8 * i, 1);
    asm volatile("fence.mbarrier_init.release.cluster;" ::: "memory");
    mbar_expect_tx(bar_full1, G1_TX);
    tma_load2d(sb + x_off(0), &tm_x, kcol(0), tt * 128, bar_full1);
    tma_load3d(sb + w1_off(0), &tm_w1, 0, kcol(0), sl * 3, bar_full1);
    tma_load3d(sb + w1_off(0) + 12288, &tm_w1, 0, kcol(0) + 32, sl * 3, bar_full1);
    TS(2);
  }
  if (warp >= 8) {
    if (tid == 256) {
      mbar_init(bar_par, 1);
      asm volatile("fence.mbarrier_init.release.cluster;" ::: "memory");
      mbar_expect_tx(bar_par, 11520 + 384 + 320);
    }
    const int a = warp - 8;
    const bf16* pp = a == 6 ? p.b1 + sl * 192 : a == 7 ? p.b2 + dq * 160 : (&p.Are)[a] + 5 * cta * NM_;
    const uint32_t dst = sb + (a == 6 ? SM_B1 : a == 7 ? SM_B2 : SM_KT + a * 384);
    named_bar(5, 256);
    if (lane == 0) {
      if (a < 6) {
#pragma unroll
        for (int i = 0; i < 5; i++) bulk_load(dst + ((i + 1) % 5) * KT_BYTES, pp + ((i + 1) % 5) * NM_, 384, bar_par);
      } else bulk_load(dst, pp, a == 6 ? 384 : 320, bar_par);
      TS(12);
    }
    __syncwarp();
  }
  if (tid == 96) {
    for (int i = 0; i < G1_STAGES; i++) { mbar_init(bar_empty1 + 8 * i, 16); mbar_init(bar_emptyx + 8 * i, 8); }
    for (int i = 0; i < 5; i++) { mbar_init(bar_full2 + 8 * i, 1); mbar_init(bar_empty2 + 8 * i, 8); }
    mbar_init(bar_ring, 8);
    mbar_init(bar_at, 2);
    mbar_init(bar_sf, 2);
    mbar_init(bar_rp, 1);
    mbar_init(bar_slab, 4);
    mbar_init(bar_u, 1);
    mbar_init(bar_k4, 2);
    mbar_init(bar_k4 + 8, 1);
    mbar_init(bar_fin, 4);
    asm volatile("fence.mbarrier_init.release.cluster;" ::: "memory");
  }
  if (tid >= 320 && tid < 504) {
    const int r = tid - 320;
    uint32_t m;
    if (r < 160) {
      const int arr = (r >> 3) & 3, z0 = 8 * (r >> 5) - 16 - (r & 7);
      const int lo = arr == 0 ? -2 : arr == 1 ? 3 : arr == 2 ? -4 : -3, hi = arr == 1 ? 5 : -lo;
      m = (uint32_t)((((2ull << (hi - lo)) - 1) << (lo - z0 + 24)) >> 24);
    } else {
      const int v = 175 - r;
      m = v >= 0 && v < 8 ? 1u << (__brev(v) >> 29) : 0u;
    }
    const uint32_t one = r < 160 ? 0x3f80u : 0x3c00u;
    uint32_t w[4];
#pragma unroll
    for (int i = 0; i < 4; i++) w[i] = ((m >> (2 * i)) & 1) * one + ((m >> (2 * i + 1)) & 1) * (one << 16);
    sts128u(sb + SM_WINA + r * 16, w[0], w[1], w[2], w[3]);
    fence_async_smem();
  }
  cluster_arrive();
  cluster_wait();
  if (tid == 128) TS(13);

  const int wg = warp >> 2, w4 = warp & 3, g = lane >> 2;
  const unsigned ep1 = p.epoch[cta] + 1;
  const uint32_t ws = wg == 2 ? SM_WS2 : SM_WS3;
  auto zero_blocks = [&]() {
    const uint32_t za = sb + ws + (tid & 127) * 16;
    sts128u(za, 0, 0, 0, 0);
    sts128u(za + 2048, 0, 0, 0, 0);
    if ((tid & 127) < 56) sts128u(za + 88 * 144, 0, 0, 0, 0);
  };
  unsigned* const hfl = p.flag + ((T2 ^ wg) * 8 + sl) * 8;
  auto h_done = [&]() {
    bulk_wait<1>();
    red_relaxed_add(hfl + 1, 1);
    bulk_wait<0>();
    red_relaxed_add(hfl + 2, 1);
    if (tid == 0) TS(5);
  };
  if (warp < 8) {
    float acc[96];
#pragma unroll
    for (int i = 0; i < 96; i++) acc[i] = 0.f;
    if (tid == 32) {
#pragma unroll
      for (int kb = XE > 1 ? 2 : 1; kb < G1_STAGES; kb++)
        tma_load3d_mc(sb + w1_off(kb) + rk * 12288, &tm_w1, 0, kcol(kb) + rk * 32, sl * 3, bar_full1 + 8 * kb);
    }
    if (!XE && tid == 128) {
#pragma unroll
      for (int kb = 1; kb < G1_STAGES; kb++) {
        mbar_expect_tx(bar_full1 + 8 * kb, G1_TX);
        tma_load2d(sb + x_off(kb), &tm_x, kcol(kb), tt * 128, bar_full1 + 8 * kb);
      }
    }
    if (tid == 64) { prefetch_tmap(&tm_hst); prefetch_tmap(&tm_hld); prefetch_tmap(&tm_w2); prefetch_tmap(&tm_ut); }
    if (tid == 96) { prefetch_tmap(&tm_aT); prefetch_tmap(&tm_u0); prefetch_tmap(&tm_out); }
    __syncwarp();
    {
      uint64_t da0 = make_desc(SB0 + ((T2 ^ wg) & 1) * 8192, 16, 1024, 1);
      const uint64_t db0 = make_desc(SB0, 4096, 1024, 1);
      const uint32_t rel = bar_empty1 + (lane == 1 ? peer_off : lane * 12);
      auto serve = [&](int kb) {
        const int so = kb % 3;
        if (lane == 0) {
          TR(160 + 16 * w4 + kb);
          if (kb >= 7) {
            const int q = w4 ? kb - 7 : 2;
            mbar_expect_tx(bar_full2 + q * 8, 20480);
#pragma unroll
            for (int i = 0; i < 2; i++)
              tma_load3d_mc(sb + SM_W2 + q * G2_TX + rk * 10240 + i * 5120, &tm_w2, 0, (3 * sl + q) * 64 + rk * 32 + i * 16, dq * 5, bar_full2 + q * 8);
          } else if (w4) {
            tma_load3d_mc(sb + w1_off(so) + rk * 12288, &tm_w1, 0, kcol(kb + 3) + rk * 32, sl * 3, bar_full1 + so * 8);
          } else {
            mbar_expect_tx(bar_full1 + so * 8, G1_TX);
            tma_load2d(sb + x_off(so), &tm_x, kcol(kb + 3), tt * 128, bar_full1 + so * 8);
          }
        }
        __syncwarp();
      };
      auto ut_store = [&](int i) {
        if (i == 0) mbar_wait(bar_slab, 0);
        if (lane == 0) {
          tma_store3d(&tm_ut, sb + SM_SLAB + i * 4096, 0, 80 * sl + i * 16, 2 * tt);
          bulk_commit();
          if (i == 3) l2_prefetch(p.w2 + (size_t)cta * 7680, 15360);
        }
        __syncwarp();
      };
      unsigned ucnt = 0;
      const uint32_t ebar = warp == 5 ? bar_empty1 : bar_emptyx;
#pragma unroll
      for (int kk = 0; kk < 10; kk++) {
        const int kb = kk - 1, so = (kk + 2) % 3, ph = (kb / 3) & 1;
        const uint32_t fb = bar_full1 + (kk % 3) * 8, eb = (kb == 8 ? bar_empty1 : ebar) + so * 8;
        bool late = kk == 0, todo = kk && (warp == 5 || (warp == 4 && kb != 7));
        if (kk) {
          late = !mbar_try(fb, (kk / 3) & 1);
          if (late) {
            wg_wait<0>();
            if (lane < 3) mbar_arrive_cluster(rel + so * 8);
            if (todo && !((kb == 0 || kb == 8) && !w4)) {
              if (mbar_wait2(eb, ph, fb, (kk / 3) & 1)) { serve(kb); todo = false; }
            }
          }
        }
        if (late) mbar_wait(fb, (kk / 3) & 1);
        if (tid == 0 && kk == 0) TS(1);
        asm volatile("" : "+l"(da0));
        const uint64_t da = da0 + (x_off(kk % 3) >> 4), db = db0 + (w1_off(kk % 3) >> 4);
        if (kk >= 2 && kk <= 4 && warp == SVW) ut_store(2 * kk - 4);
        if (kk == UKB && warp == UW) {
          if (lane == 0) {
            TR(233);
            spin_ge(p.flag + (260 + (cta >> 4)) * 8, 16 * ep1, ucnt);
            TR(234);
            mbar_expect_tx(bar_u, 3 * U0_BYTES);
#pragma unroll
            for (int i = 1; i < 4; i++) tma_load4d(sb + SM_U0 + i * U0_BYTES, &tm_u0, 0, -3, 0, 5 * cta + i, bar_u);
            TR(235);
            TS(17);
          }
          __syncwarp();
        }
        if ((tid & 127) == 0) TR(16 * wg + kk);
        wg_fence();
#pragma unroll
        for (int k = 0; k < G1S; k++) wgmma_n192(acc, da + k * 2, db + (k >> 1) * 768 + (k & 1) * 128);
        wg_commit();
        if (kk == 0) {
          if (tid == 96 && tt < 14) tma_pf3d(&tm_w1, 0, kcol(3 + (tt >> 1)) + (tt & 1) * 32, sl * 3);
          __syncwarp();
        }
        if (kk) {
          wg_wait<1>();
          if (!late && lane < 3) mbar_arrive_cluster(rel + so * 8);
          if (todo) {
            if ((kb == 0 || kb == 8) && !w4) mbar_wait(kb ? bar_sf : bar_slab, 0);
            mbar_wait(eb, ph);
            serve(kb);
          }
        }
        if (kk == USTEP && warp == SVW) {
          if (lane == 0) {
            {
              bulk_wait<0>();
              red_relaxed_add(p.flag + (260 + sl) * 8, 1);
              mbar_expect_tx(bar_rp, 15360);
#pragma unroll
              for (int i = 0; i < 3; i++) tma_load3d(sb + SM_SLAB + i * 5120, &tm_w2, 0, (3 * (cta & 31) + i) * 16, (cta >> 5) * 5, bar_rp);
              TS(16);
            }
          }
          __syncwarp();
        }
        if (kk >= RPK && kk < RPK + 3 && warp == SVW) {
          if (kk == RPK) mbar_wait(bar_rp, 0);
          if (lane == 0) {
            if (kk == RPK) {
              bulk_store(p.w2p + cta * 7680, sb + SM_SLAB, 15360);
              bulk_commit();
            } else if (kk == RPK + 1) {
              bulk_wait_read0();
              mbar_arrive(bar_sf);
              mbar_arrive_cluster(bar_sf + peer_off);
            } else {
              bulk_wait<0>();
              red_relaxed_add(p.flag + (268 + (cta >> 5)) * 8, 1);
              TS(19);
            }
          }
          __syncwarp();
        }
        if ((kk == 2 || kk == 3) && warp == SVW) ut_store(2 * kk - 3);
        if (kk == UKB - 1 && tid == 32 * UW) ucnt = ld_relaxed(p.flag + (260 + (cta >> 4)) * 8);
        wg_fence();
#pragma unroll
        for (int k = G1S; k < 4; k++) wgmma_n192(acc, da + k * 2, db + (k >> 1) * 768 + (k & 1) * 128);
        wg_commit();
      }
      wg_wait<0>();
      if ((tid & 127) == 96) TR(224 + 4 * wg);
      if (lane == 2) mbar_arrive_cluster(rel);
    }
    mbar_wait(bar_emptyx + 8 - 8 * wg, wg);
    if (wg) mbar_wait(bar_sf, 0);
    mbar_wait(bar_par, 0);
    if ((tid & 127) == 96) TR(225 + 4 * wg);
    const int mrow = w4 * 16 + (lane & 7) + ((lane >> 3) & 1) * 8;
    const bf162 one2 = __float2bfloat162_rn(1.f);
    const uint32_t stg = sb + (wg ? SM_W2 + 3 * G2_TX : 0), sts = wg ? 8192 : G2_TX;
    uint32_t bb[24];
    const uint32_t ba = sb + SM_B1 + (lane >> 3) * 16;
    ldsm4(ba, bb);
    ldsm4(ba + 64, bb + 4);
#pragma unroll
    for (int j = 0; j < 24; j += 2) {
      uint32_t r[4];
      if (j == 16) mbar_wait(bar_emptyx + 16, 0);
      if (j < 16 && (j & 2)) ldsm4(ba + (j + 6) * 16, bb + j + 6);
#pragma unroll
      for (int q = 0; q < 4; q++) {
        const int jj = j + (q >> 1);
        bf162 v = as_bf162(pack_bf16(acc[4 * jj + 2 * (q & 1)], acc[4 * jj + 2 * (q & 1) + 1]));
        v = __hfma2_relu(v, one2, as_bf162(bb[jj]));
        r[q] = as_u32(__hmul2_rn(v, v));
      }
      const int chunk = (j & 7) + (lane >> 4);
      stsm_x4(stg + (j >> 3) * sts + mrow * 128 + ((chunk ^ (mrow & 7)) << 4), r[0], r[1], r[2], r[3]);
      if (j < 4 && (tid & 127) == 96) TR(226 + 4 * wg + (j >> 1));
      if ((j & 7) == 6) {
        if ((tid & 127) == 96) TR(16 * wg + 10 + 2 * (j >> 3));
        fence_async_smem();
        __syncwarp();
        if ((tid & 127) == 96) TR(16 * wg + 11 + 2 * (j >> 3));
        if (lane == 0) {
          tma_store2d(&tm_hst, stg + (j >> 3) * sts + w4 * 2048, 0, (sl * 3 + (j >> 3)) * L_ + (T2 ^ wg) * 64 + w4 * 16);
          bulk_commit();
        }
      }
    }
    if (lane == 0) {
      if (tid == 0) TS(4);
      bulk_wait<2>();
      red_relaxed_add(hfl, 1);
      if (wg) {
        bulk_wait_read0();
        mbar_arrive(bar_ring);
        mbar_arrive_cluster(bar_ring + peer_off);
        if (w4 > 1) h_done();
      }
    }
    __syncwarp();
  } else {
    const int wgs = wg & 1, gam = w4 >> 1, slot = (w4 & 1) * 32 + lane;
    const int ch0 = 3 - 2 * wgs + gam;
    const uint32_t ldt[2] = {ldg16(p.logdt + 5 * cta + ch0), ldg16(p.logdt + 5 * cta)};
    const uint32_t kgo = wgs ? SM_KG3 : SM_KG2, kgA = sb + kgo;
    const uint32_t ksa = kgA + gam * 8192 + (slot >> 3) * 256 + (slot & 7) * 16, ksb = ksa + KG_B - gam * 2048;
    const uint64_t dka = make_desc(SB0 + kgo, 128, 2048, 0), dkb = dka + (KG_B >> 4);
    const uint32_t kt0 = sb + SM_KT + ch0 * KT_BYTES, kt4 = sb + SM_KT;
    if (tid < 261) { const uint32_t dk = ldg16(p.Dsk + 5 * cta + tid - 256); sts32(sb + SM_DSK + (tid - 256) * 4, dk | (dk << 16)); }
    float dt = __bfloat162float(__float2bfloat16_rn(expf(bf_lo(ldt[0])))), dt4 = __bfloat162float(__float2bfloat16_rn(expf(bf_lo(ldt[1]))));
    float acc[24], cs, sc;
#pragma unroll
    for (int i = 0; i < 24; i++) acc[i] = 0.f;
    uint32_t po = kt0 + slot * 2;
    asm volatile("" : "+f"(dt), "+f"(dt4), "+r"(po));
    if (wgs) {
      const uint32_t o = sb + SM_SLAB + (lane >> 4) * 2048 + (lane & 7) * 128 + ((((lane & 8) >> 1) + w4) ^ (lane & 7)) * 16;
      uint32_t r[24], oj[6];
#pragma unroll
      for (int h = 0; h < 2; h++) {
        mbar_wait(bar_full1 + 8 * h, 0);
        if (tid == 384 && h) TR(240);
#pragma unroll
        for (int j = 0; j < 6 - 2 * h; j++) {
          const int jj = ksw ? 9 - j - 6 * h : j + 6 * h, c8 = ((10 * sl) & 7) + jj;
          ldsm4t(sb + ((c8 >> 3) ^ ksw ? x_off(1) : x_off(0)) + (32 * w4 + lane) * 128 + (((c8 ^ lane) & 7) << 4), r + 4 * j);
          oj[j] = o + (jj >> 1) * 4096 + (jj & 1) * 1024;
        }
#pragma unroll
        for (int j = 0; j < 6 - 2 * h; j++) stsm_x4(oj[j], r[4 * j], r[4 * j + 1], r[4 * j + 2], r[4 * j + 3]);
      }
      fence_async_smem();
      __syncwarp();
      if (lane == 0) mbar_arrive(bar_slab);
      if (tid == 384) TR(241);
    }
    mbar_wait(bar_par, 0);
    if (tid == 256) TS(14);
    bc_scale(kt0, lane, dt, cs, sc);
#define PIN2(v) asm volatile("" : "+f"((v).x), "+f"((v).y))
#define PIN(v) asm volatile("" : "+r"(*reinterpret_cast<uint32_t*>(&(v).re)), "+r"(*reinterpret_cast<uint32_t*>(&(v).im)))
#pragma unroll 1
    for (int s = 0; s < (wgs ? 3 : 5); s++) {
      if ((tid & 127) == 0) TR(64 + 20 * wgs + 4 * s);
      wg_fence();
      KS wgmma_n48_tt(acc, dka, dkb, s != 1 && s != 4);
      KS wgmma_n48_tt(acc, dka + 16, dkb + 16, 1);
      float ar2 = dt * 1.4426950409f * bf_lo(lds16(po)), ai = dt * bf_lo(lds16(po + 384));
      float2 cc = cmul(make_float2(bf_lo(lds16(po + 1536)), bf_lo(lds16(po + 1920))), make_float2(bf_lo(lds16(po + 768)), bf_lo(lds16(po + 1152))));
      cc.x *= cs; cc.y *= -cs;
      float2 e1 = cexp2(ar2, ai);
      PIN2(e1); PIN2(cc);
      KS wgmma_n48_tt(acc, dka + 32, dkb + 32, 1);
      KS wgmma_n48_tt(acc, dka + 48, dkb + 48, 1);
      asm volatile("" : "+f"(ar2), "+f"(ai));
      float2 e64 = cexp2(64.f * ar2, 64.f * ai);
      const float2 e2 = csqr(e1), e4 = csqr(e2);
      float2 e8 = csqr(e4), c4 = cmul(cc, make_float2(e4.x, -e4.y));
      PIN2(e64); PIN2(e8); PIN2(c4);
      KS wgmma_n48_tt(acc, dka + 64, dkb + 64, 1);
      KS wgmma_n48_tt(acc, dka + 80, dkb + 80, 1);
      PIN2(e64); PIN2(e8);
      const float2 e16 = csqr(e8), e128 = csqr(e64), h1 = csqr(e128);
      float2 e32 = csqr(e16), h2 = csqr(h1);
      PIN2(e32); PIN2(h2);
      KS wgmma_n48_tt(acc, dka + 96, dkb + 96, 1);
      KS wgmma_n48_tt(acc, dka + 112, dkb + 112, 1);
      wg_commit();
      if ((tid & 127) == 0) TR(64 + 20 * wgs + 4 * s + 1);
      HC va[8], vb[8];
      const __half2 g32 = __floats2half2_rn(e32.x, e32.y), g64 = __floats2half2_rn(e64.x, e64.y), g128 = __floats2half2_rn(e128.x, e128.y);
      const __half2 f1 = __floats2half2_rn(e1.x, e1.y), fh1 = __floats2half2_rn(h1.x, h1.y), fh2 = __floats2half2_rn(h2.x, h2.y);
      const __half2 f4 = __floats2half2_rn(e4.x, e4.y);
      va[0].re = __floats2half2_rn(1.f, e8.x); va[0].im = __floats2half2_rn(0.f, e8.y);
      va[1] = hmul(va[0], __floats2half2_rn(e16.x, e16.y));
      vb[0].re = __floats2half2_rn(cc.x, c4.x); vb[0].im = __floats2half2_rn(cc.y, c4.y);
      vb[1] = hmulc(vb[0], __floats2half2_rn(e2.x, e2.y));
      va[2] = hmul(va[0], g32); va[3] = hmul(va[1], g32);
      vb[2] = hmulc(vb[0], f1); vb[3] = hmulc(vb[1], f1);
      PIN(va[2]); PIN(va[3]); PIN(vb[2]); PIN(vb[3]);
      if (s == 3) {
        const uint32_t za = sb + SM_KT + 3 * KT_BYTES + (tid & 127) * 16;
        sts128u(za, 0, 0, 0, 0); sts128u(za + KT_BYTES, 0, 0, 0, 0);
      }
      if ((tid & 127) == 0) TR(64 + 20 * wgs + 4 * s + 2);
      wg_wait<0>();
      named_bar(1 + wg, 128);
      if ((tid & 127) == 0) TR(64 + 20 * wgs + 4 * s + 3);
      st_hc4(ksa, va);
      PIN(va[0]);
#pragma unroll
      for (int i = 0; i < 4; i++) va[4 + i] = hmul(va[i], g64);
      st_hc4(ksb, vb);
      PIN(va[0]);
#pragma unroll
      for (int i = 0; i < 4; i++) va[i] = hmul(va[i], g128);
      st_hc4(ksa + 2048, va + 4);
      PIN(va[4]);
#pragma unroll
      for (int i = 4; i < 8; i++) va[i] = hmul(va[i], g128);
      st_hc4(ksa + 4096, va);
      PIN(vb[0]);
      vb[4] = hmulc(vb[0], fh1); vb[5] = hmulc(vb[1], fh1);
      vb[6] = vb[4]; vb[7] = hmulc(vb[4], f4);
      st_hc4(ksa + 6144, va + 4);
      PIN(vb[7]);
      vb[0] = hmulc(vb[7], fh1); vb[1] = hmulc(vb[7], fh2);
      vb[2].re = __highs2half2(vb[0].re, vb[1].re); vb[2].im = __highs2half2(vb[0].im, vb[1].im);
      vb[2] = hmulc(vb[2], fh2);
      vb[3] = hmulc(vb[2], fh2);
      st_hc4(ksb + 2048, vb + 4);
      st_hc4(ksb + 4096, vb);
      po += 128;
      if (!wgs && s == 2) {
        po = kt4 + (96 * gam + slot) * 2;
        dt = dt4;
        bc_scale(kt4, lane, dt, cs, dt4);
      }
      if ((tid & 127) == 0) TR(200 + 16 * wgs);
      fence_async_smem();
      if ((tid & 127) == 0) TR(201 + 16 * wgs);
      named_bar(1 + wg, 128);
      if ((tid & 127) == 0) TR(202 + 16 * wgs);
      if (s == 3) {
        float kv[12];
#pragma unroll
        for (int i = 0; i < 12; i++) kv[i] = gam ? acc[12 + i] : acc[i];
        kt_store(kt0, sb + SM_DUMP, w4 & 1, lane, kv, sc, 5 * cta + ch0);
        if (tid == 256) TS(15);
      }
      __syncwarp();
    }
#define TK(i) if ((tid & 127) == 0) TR(192 + 16 * wgs + (i))
    TK(0);
    wg_fence();
#pragma unroll
    for (int ks = 0; ks < 4; ks++) wgmma_n48_tt(acc, dka + ks * 16, dkb + ks * 16, 1);
    if (wgs) {
#pragma unroll
      for (int ks = 4; ks < 8; ks++) wgmma_n48_tt(acc, dka + ks * 16, dkb + ks * 16, 1);
    }
    wg_commit();
    {
      const uint32_t za = sb + SM_KT + wgs * KT_BYTES + (tid & 127) * 16;
      sts128u(za, 0, 0, 0, 0);
      if (wgs) sts128u(za + KT_BYTES, 0, 0, 0, 0);
    }
    TK(1);
    wg_wait<0>();
    named_bar(1 + wg, 128);
    TK(2);
    {
      float kv[12];
#pragma unroll
      for (int i = 0; i < 12; i++) kv[i] = gam ? acc[12 + i] : acc[i];
      if (!wgs) {
        const uint32_t xa = sb + SM_WS2 + WS_X2 + ((w4 & 1) * 32 + lane) * 48;
        if (gam) {
          sts128f(xa, kv[0], kv[1], kv[2], kv[3]); sts128f(xa + 16, kv[4], kv[5], kv[6], kv[7]); sts128f(xa + 32, kv[8], kv[9], kv[10], kv[11]);
        }
        named_bar(1 + wg, 128);
        if (!gam) {
#pragma unroll
          for (int i = 0; i < 3; i++) {
            const float4 o = lds128f(xa + 16 * i);
            kv[4 * i] += o.x; kv[4 * i + 1] += o.y; kv[4 * i + 2] += o.z; kv[4 * i + 3] += o.w;
          }
        }
      }
      if (wgs || !gam) kt_store(wgs ? kt0 : kt4, sb + SM_DUMP, w4 & 1, lane, kv, wgs ? sc : dt4, 5 * cta + (wgs ? ch0 : 0));
    }
    TK(3);
    zero_blocks();
    fence_async_smem();
    TK(4);
    if (tid == 256) TS(18);
  }

  if (wg > 1) {
    named_bar(1 + wg, 128);
    if ((tid & 127) == 0) TR(197 + 16 * (wg & 1));
    if (tid == 256) mbar_arrive(bar_k4);
    mbar_wait(bar_u, 0);
    if (tid == 384) TS(20);
#pragma unroll 1
    for (int i = 0; i < wg; i++) {
      const int ch = i == 2 ? 0 : 7 - 2 * wg + i;
      const uint32_t u0 = SM_U0 + ch * U0_BYTES;
      const uint32_t tq = tid == TQ_TID && i < 2 ? sb + SM_TR + 512 + (i & 1) * 64 : 0u;
      if ((tid & 127) == 0) TR(32 + wg * 4 + i);
      if (i == wg - 1) mbar_wait(bar_k4 + 24 - 8 * wg, 0);
      conv(sb, ws, u0, SM_KT + ch * KT_BYTES, 1 + wg, lds32(sb + SM_DSK + ch * 4), w4, lane, tq, [&]() {
        if ((tid & 127) == 64 && i == 0) {
          mbar_expect_tx(bar_k4 + 24 - 8 * wg, U0_BYTES);
          tma_load4d(sb + SM_U0 + (wg == 3 ? 0 : 4 * U0_BYTES), &tm_u0, 0, -3, 0, 5 * cta + (wg == 3 ? 0 : 4), bar_k4 + 24 - 8 * wg);
        }
        __syncwarp();
      });
      fence_async_smem();
      TQ(14);
      named_bar(1 + wg, 128);
      TQ(15);
      if ((tid & 127) == 0) {
        bulk_store(p.aT + (5 * cta + ch) * L_, sb + u0, 4096);
        bulk_commit();
      }
      __syncwarp();
    }
    if ((tid & 127) == 0) TR(32 + wg * 4 + 3);
    if ((tid & 127) == 0) {
      bulk_wait<0>();
      red_relaxed_add(p.flag + (256 + (cta >> 5)) * 8, wg);
      TS(20 + wg);
    }
    __syncwarp();
  }

  if (wg == 0) {
    float acc[80];
#pragma unroll
    for (int i = 0; i < 80; i++) asm volatile("" : "=f"(acc[i]));
    {
      const uint64_t da0 = make_desc(SB0, 16, 1024, 1);
      const uint64_t db0 = make_desc(SB0 + SM_W2, 1024, 512, 2);
      const uint32_t rel = bar_empty2 + (lane ? peer_off : 0u);
      named_bar(1, 128);
#pragma unroll
      for (int kb = 0; kb < 24; kb++) {
        const int so = kb % 5, ph = (kb / 5) & 1, prev = (kb + 4) % 5;
        bool late = false;
        if (kb > 2 && kb < 20) {
          late = !mbar_try(bar_full2 + so * 8, ph);
          if (late) {
            wg_wait<0>();
            if (lane < 2) mbar_arrive_cluster(rel + prev * 8);
          }
        }
        if (late || kb <= 2 || kb >= 20) mbar_wait(bar_full2 + so * 8, ph);
        if (tid == 0 && kb == 0) TS(7);
        if (tid == 0 && kb == 12) TS(8);
        if (tid == 0) TR(96 + kb);
        const uint64_t da = da0 + so * (G2_TX >> 4), db = db0 + so * (G2_TX >> 4);
        wg_fence();
#pragma unroll
        for (int k = 0; k < G2S; k++) wgmma_n160(acc, da + k * 2, db + k * 320, kb + k);
        wg_commit();
        if (kb > 0 && kb <= 20) {
          wg_wait<1>();
          if (kb == 20) {
            if (lane == 0) mbar_arrive(bar_fin);
          } else if (lane < 2 && !late) mbar_arrive_cluster(rel + prev * 8);
        }
        wg_fence();
#pragma unroll
        for (int k = G2S; k < 4; k++) wgmma_n160(acc, da + k * 2, db + k * 320, kb + k);
        wg_commit();
        if (kb == 0) {
          if (lane == 0) h_done();
          __syncwarp();
        }
      }
    }
    uint32_t bb[20], a[40];
#pragma unroll
    for (int j = 0; j < 5; j++) ldsm4(sb + SM_B2 + (lane >> 3) * 16 + j * 64, bb + 4 * j);
    wg_wait<0>();
    if (tid == 0) TS(9);
    named_bar(1, 128);
    uint32_t r[40];
#pragma unroll
    for (int i = 0; i < 40; i++) r[i] = as_u32(__hadd2_rn(as_bf162(pack_bf16(acc[2 * i], acc[2 * i + 1])), as_bf162(bb[i >> 1])));
#pragma unroll
    for (int i = 0; i < 40; i += 8) asm volatile("" : "+r"(r[i]), "+r"(r[i + 1]), "+r"(r[i + 2]), "+r"(r[i + 3]), "+r"(r[i + 4]), "+r"(r[i + 5]), "+r"(r[i + 6]), "+r"(r[i + 7]));
    const uint32_t al = sb + SM_AT + ((lane >> 4) * 8 + (lane & 7)) * 128 + (((2 * w4 + ((lane >> 3) & 1)) ^ (lane & 7) ^ (T2 & 7)) << 4);
    const uint32_t ol = sb + SM_OUT + w4 * 5120 + (lane & 15) * 64;
    mbar_wait(bar_at, 0);
    if (tid == 0) TS(11);
    const bf162 one2 = __float2bfloat162_rn(1.f);
    const bf162 ga = as_bf162(lds32(sb + SM_G + (w4 * 16 + g) * 4)), gb = as_bf162(lds32(sb + SM_G + (w4 * 16 + g + 8) * 4));
#pragma unroll
    for (int j = 0; j < 10; j++) ldsm4t(al + j * 2048, a + 4 * j);
    const bf162 na = __hsub2_rn(one2, ga), nb = __hsub2_rn(one2, gb);
#pragma unroll
    for (int j = 0; j < 20; j += 2) {
#pragma unroll
      for (int i = 2 * j; i < 2 * j + 4; i++)
        r[i] = as_u32(__hadd2_rn(__hmul2_rn(as_bf162(a[i]), (i & 1) ? gb : ga), __hmul2_rn(as_bf162(r[i]), (i & 1) ? nb : na)));
      stsm_x4(ol + (j >> 2) * 1024 + ((((j & 2) + (lane >> 4)) ^ ((lane >> 1) & 3)) << 4), r[2 * j], r[2 * j + 1], r[2 * j + 2], r[2 * j + 3]);
    }
    fence_async_smem();
    __syncwarp();
    if (lane == 0) {
      tma_store3d(&tm_out, sb + SM_OUT + w4 * 5120, 0, T2 * 64 + w4 * 16, dq * 5);
      bulk_commit();
      if (tid == 0) p.epoch[cta] = ep1;
      bulk_wait_read0();
      if (tid == 0) TS(10);
    }
  } else if (warp == 4 || warp == 5) {
    const unsigned* fl = p.flag + (w4 ? (T2 * 8 + (lane & 7)) * 8 + min(lane >> 3, 2) : (268 + dq) * 8);
    const unsigned need = (w4 ? 4 : 32) * ep1;
    const bf16* wsrc = p.w2p + dq * (24 * 10240) + rk * 5120;
    unsigned rdy = __ballot_sync(0xffffffffu, (int)(ld_relaxed(fl) - need) >= 0);
    if (lane == 0) h_done();
    __syncwarp();
    uint32_t so = 3, ph = 1, ki = sl == 0;
#pragma unroll 1
    for (int q = 3; q < 24; q++) {
      const int kx = 3 * (ki & 7) + (ki >> 3);
#pragma unroll 1
      for (int it = 0; !((rdy >> ki) & 1); ++it) {
        rdy = __ballot_sync(0xffffffffu, (int)(ld_relaxed(fl) - need) >= 0);
        if (it > SPIN_LIMIT) SPIN_FAIL;
      }
      if (q == 3 + w4) mbar_wait(bar_ring, 0);
      mbar_wait(bar_empty2 + so * 8, ph);
      if (lane == 0) {
        if (w4) tma_load2d(sb + so * G2_TX, &tm_hld, 0, kx * L_ + T2 * 64, bar_full2 + so * 8);
        else {
          mbar_expect_tx(bar_full2 + so * 8, G2_TX);
          bulk_load_mc(sb + SM_W2 + so * G2_TX + rk * 10240, wsrc + kx * 10240, 10240, bar_full2 + so * 8);
        }
        if (q == 3 && w4) TS(6);
      }
      __syncwarp();
      if (++so == 5) { so = 0; ph ^= 1; }
      ki += ((ki + 1) & 7) == sl ? 2 : 1;
    }
  } else if (wg == 1) {
#pragma unroll 1
    for (int r = 0; r < 2; r++) {
      const int t = T2 * 64 + dq * 16 + (w4 & 1) * 8 + r * 4 + (lane >> 3);
      const uint4* xr = (const uint4*)(p.u + (size_t)t * D_) + (lane & 7);
      const uint4* gw = (const uint4*)p.gate_w + (lane & 7);
      uint4 xv[10], gv[10];
#pragma unroll
      for (int i = 0; i < 10; i++) { xv[i] = __ldg(xr + 8 * i); gv[i] = __ldg(gw + 8 * i); }
      float s0 = 0.f, s1 = 0.f;
#pragma unroll
      for (int i = 0; i < 10; i++) {
        const uint32_t a = as_u32(__hmul2_rn(as_bf162(xv[i].x), as_bf162(gv[i].x))), b = as_u32(__hmul2_rn(as_bf162(xv[i].y), as_bf162(gv[i].y)));
        const uint32_t d = as_u32(__hmul2_rn(as_bf162(xv[i].z), as_bf162(gv[i].z))), e = as_u32(__hmul2_rn(as_bf162(xv[i].w), as_bf162(gv[i].w)));
        s0 += (bf_lo(a) + bf_hi(a)) + (bf_lo(b) + bf_hi(b));
        s1 += (bf_lo(d) + bf_hi(d)) + (bf_lo(e) + bf_hi(e));
      }
      s0 += s1;
#pragma unroll
      for (int o = 4; o; o >>= 1) s0 += __shfl_xor_sync(0xffffffffu, s0, o);
      if ((lane & 7) == 0) {
        const float z = __bfloat162float(__float2bfloat16_rn(s0));
        st_relaxed(p.gate + t, (ep1 << 16) | (pack_bf16(1.f / (1.f + __expf(-z)), 0.f) & 0xffffu));
      }
    }
    if (warp == 6) {
      unsigned v0 = 0, v1 = 0;
#pragma unroll 1
      for (int it = 0;; ++it) {
        v0 = ld_relaxed(p.gate + T2 * 64 + lane);
        v1 = ld_relaxed(p.gate + T2 * 64 + 32 + lane);
        if (__all_sync(0xffffffffu, ((v0 ^ (ep1 << 16)) | (v1 ^ (ep1 << 16))) < 65536u)) break;
        __nanosleep(200);
        if (it > SPIN_LIMIT) SPIN_FAIL;
      }
      sts32(sb + SM_G + lane * 4, __byte_perm(v0, 0, 0x1010));
      sts32(sb + SM_G + 128 + lane * 4, __byte_perm(v1, 0, 0x1010));
      __syncwarp();
      if (lane == 0) mbar_arrive(bar_at);
    }
    if (tid == 224) {
      mbar_wait(bar_fin, 0);
#pragma unroll 1
      for (int it = 0; (int)(ld_relaxed(p.flag + (256 + dq) * 8) - 160 * ep1) < 0; ++it) {
        if (it > SPIN_LIMIT) SPIN_FAIL;
      }
      TS(24);
      mbar_expect_tx(bar_at, 20480);
      tma_load2d(sb + SM_AT, &tm_aT, T2 * 64, dq * 160, bar_at);
    }
  }
}

#define PROM2 CU_TENSOR_MAP_L2_PROMOTION_L2_128B
#define PROM3 CU_TENSOR_MAP_L2_PROMOTION_L2_128B
typedef CUresult (*EncodeFn)(CUtensorMap*, CUtensorMapDataType, cuuint32_t, void*, const cuuint64_t*, const cuuint64_t*,
                             const cuuint32_t*, const cuuint32_t*, CUtensorMapInterleave, CUtensorMapSwizzle,
                             CUtensorMapL2promotion, CUtensorMapFloatOOBfill);

static void make_map(EncodeFn fn, CUtensorMap* m, const void* ptr, uint64_t inner, uint64_t outer, uint32_t box_in, uint32_t box_out,
                     CUtensorMapSwizzle swz) {
  cuuint64_t dims[2] = {inner, outer};
  cuuint64_t strides[1] = {inner * 2};
  cuuint32_t box[2] = {box_in, box_out};
  cuuint32_t es[2] = {1, 1};
  CUresult r = fn(m, CU_TENSOR_MAP_DATA_TYPE_BFLOAT16, 2, const_cast<void*>(ptr), dims, strides, box, es, CU_TENSOR_MAP_INTERLEAVE_NONE, swz,
     PROM2, CU_TENSOR_MAP_FLOAT_OOB_FILL_NONE);
  (void)r;
}

static void make_map3(EncodeFn fn, CUtensorMap* m, const void* ptr, uint64_t d0, uint64_t d1, uint64_t d2, uint64_t s1, uint64_t s2,
                      uint32_t b0, uint32_t b1, uint32_t b2, CUtensorMapSwizzle swz) {
  cuuint64_t dims[3] = {d0, d1, d2};
  cuuint64_t strides[2] = {s1, s2};
  cuuint32_t box[3] = {b0, b1, b2};
  cuuint32_t es[3] = {1, 1, 1};
  CUresult r = fn(m, CU_TENSOR_MAP_DATA_TYPE_BFLOAT16, 3, const_cast<void*>(ptr), dims, strides, box, es, CU_TENSOR_MAP_INTERLEAVE_NONE, swz,
     PROM3, CU_TENSOR_MAP_FLOAT_OOB_FILL_NONE);
  (void)r;
}

extern "C" void kernel_launch(void* const* d_in, const int* in_sizes, int n_in, void* d_out, int out_size) {
  static EncodeFn fn = nullptr;
  static CUtensorMap tm_x, tm_w1, tm_ut, tm_hst, tm_hld, tm_w2, tm_aT, tm_u0, tm_out;
  static void *pg = nullptr, *pf = nullptr, *pep = nullptr, *pa = nullptr, *pw = nullptr;
  static const void *c_x = nullptr, *c_w1 = nullptr, *c_w2 = nullptr, *c_out = nullptr;
  if (!fn) {
    void* f = nullptr;
    cudaDriverEntryPointQueryResult qr;
    cudaGetDriverEntryPoint("cuTensorMapEncodeTiled", &f, cudaEnableDefault, &qr);
    fn = (EncodeFn)f;
    cudaFuncSetAttribute(fused_kernel, cudaFuncAttributeMaxDynamicSharedMemorySize, SMEM_BYTES);
    void *ph, *pu;
    cudaGetSymbolAddress(&ph, g_h);
    cudaGetSymbolAddress(&pa, g_aT);
    cudaGetSymbolAddress(&pu, g_uT);
    cudaGetSymbolAddress(&pw, g_w2p);
    cudaGetSymbolAddress(&pg, g_gate);
    cudaGetSymbolAddress(&pf, g_flag);
    cudaGetSymbolAddress(&pep, g_epoch);
    make_map(fn, &tm_hst, ph, 64, 24 * L_, 64, 16, CU_TENSOR_MAP_SWIZZLE_128B);
    make_map(fn, &tm_hld, ph, 64, 24 * L_, 64, 64, CU_TENSOR_MAP_SWIZZLE_128B);
    make_map(fn, &tm_aT, pa, L_, D_, 64, 160, CU_TENSOR_MAP_SWIZZLE_128B);
    make_map3(fn, &tm_ut, pu, 64, D_, 32, 4096, 128, 64, 16, 2, CU_TENSOR_MAP_SWIZZLE_128B);
    {
      cuuint64_t dims[4] = {32, 16, 4, D_}, strides[3] = {256, 64, 4096};
      cuuint32_t box[4] = {32, 19, 4, 1}, es[4] = {1, 1, 1, 1};
      fn(&tm_u0, CU_TENSOR_MAP_DATA_TYPE_BFLOAT16, 4, pu, dims, strides, box, es, CU_TENSOR_MAP_INTERLEAVE_NONE, CU_TENSOR_MAP_SWIZZLE_NONE,
         CU_TENSOR_MAP_L2_PROMOTION_L2_256B, CU_TENSOR_MAP_FLOAT_OOB_FILL_NONE);
    }
  }
  if (c_x != d_in[0]) {
    make_map(fn, &tm_x, d_in[0], D_, L_, 64, 128, CU_TENSOR_MAP_SWIZZLE_128B);
    c_x = d_in[0];
  }
  if (c_w1 != d_in[10]) { make_map3(fn, &tm_w1, d_in[10], 64, D_, 24, F_ * 2, 128, 64, 32, 3, CU_TENSOR_MAP_SWIZZLE_128B); c_w1 = d_in[10]; }
  if (c_w2 != d_in[12]) { make_map3(fn, &tm_w2, d_in[12], 32, F_, 20, D_ * 2, 64, 32, 16, 5, CU_TENSOR_MAP_SWIZZLE_64B); c_w2 = d_in[12]; }
  if (c_out != d_out) { make_map3(fn, &tm_out, d_out, 32, L_, 20, D_ * 2, 64, 32, 16, 5, CU_TENSOR_MAP_SWIZZLE_64B); c_out = d_out; }
  Params p;
  p.u = (const bf16*)d_in[0];
  p.Are = (const bf16*)d_in[1];
  p.Aim = (const bf16*)d_in[2];
  p.Bre = (const bf16*)d_in[3];
  p.Bim = (const bf16*)d_in[4];
  p.Cre = (const bf16*)d_in[5];
  p.Cim = (const bf16*)d_in[6];
  p.logdt = (const bf16*)d_in[7];
  p.Dsk = (const bf16*)d_in[8];
  p.w1 = (const bf16*)d_in[10];
  p.b1 = (const bf16*)d_in[11];
  p.w2 = (const bf16*)d_in[12];
  p.b2 = (const bf16*)d_in[13];
  p.gate_w = (const bf16*)d_in[14];
  p.aT = (bf16*)pa;
  p.w2p = (bf16*)pw;
  p.gate = (unsigned*)pg;
  p.flag = (unsigned*)pf;
  p.epoch = (unsigned*)pep;
  fused_kernel<<<NCTA, 512, SMEM_BYTES, cudaStreamPerThread>>>(tm_x, tm_w1, tm_ut, tm_hst, tm_hld, tm_w2, tm_aT, tm_u0, tm_out, p);
}
```
